```python
import torch

def _softmax(x, axis=-1):
    return torch.softmax(x, dim=axis)
def _gelu(x):
    return torch.nn.functional.gelu(x, approximate="tanh")
def _silu(x):
    return torch.nn.functional.silu(x)
def _sigmoid(x):
    return torch.sigmoid(x)
def _layernorm(x, axis=-1, eps=1e-5):
    m = x.mean(dim=axis, keepdim=True)
    v = x.var(dim=axis, keepdim=True, unbiased=False)
    return (x - m) / torch.sqrt(v + eps)
def _scatter_add(tgt, idx, src, axis=0):
    return tgt.clone().index_add_(axis, idx, src)
def _segment_sum(src, seg, n):
    out = torch.zeros((n,) + src.shape[1:], dtype=src.dtype)
    return out.index_add_(0, seg, src)
def _pad(x, pw):
    flat = tuple(v for pair in reversed(pw) for v in pair)
    return torch.nn.functional.pad(x, flat)

kernel_name = 'standalone__cross_network_dcn__recsys'

def setup_inputs():

    _w = (lambda a: (lambda t: t.to(torch.bfloat16) if t.is_floating_point() else t)(torch.as_tensor(a)))
    B, F, D, L = 16384, 100, 16, 6
    Din = min(F * D, 1024)
    return {
        "x0": _w((lambda *s: torch.randn(*s, dtype=torch.bfloat16) * 0.05)(B, Din)),
        "ws": _w((lambda *s: torch.randn(*s, dtype=torch.bfloat16) * 0.8)(L, Din, Din) * (Din ** -0.5)),
        "bs": _w((lambda *s: torch.randn(*s, dtype=torch.bfloat16) * 3.2)(L, Din) * 0.01),
    }

def reference(x0, ws, bs):
    x = x0
    L = ws.shape[0]
    for l in range(L):
        proj = torch.einsum('bd,de->be', x, ws[l]) + bs[l]
        x = x0 * proj + x
    return x
```

```cpp
#include <cuda_runtime.h>
#include <cuda.h>
#include <cuda_bf16.h>
#include <stdint.h>

namespace dcn {

__device__ __forceinline__ void wgmma_n256(float (&d)[128], uint64_t da, uint64_t db) {
  asm volatile("wgmma.mma_async.sync.aligned.m64n256k16.f32.bf16.bf16 "
    "{%0, %1, %2, %3, %4, %5, %6, %7, %8, %9, %10, %11, %12, %13, %14, %15, %16, %17, %18, %19, %20, %21, %22, %23, %24, %25, %26, %27, %28, %29, %30, %31, %32, %33, %34, %35, %36, %37, %38, %39, %40, %41, %42, %43, %44, %45, %46, %47, %48, %49, %50, %51, %52, %53, %54, %55, %56, %57, %58, %59, %60, %61, %62, %63, %64, %65, %66, %67, %68, %69, %70, %71, %72, %73, %74, %75, %76, %77, %78, %79, %80, %81, %82, %83, %84, %85, %86, %87, %88, %89, %90, %91, %92, %93, %94, %95, %96, %97, %98, %99, %100, %101, %102, %103, %104, %105, %106, %107, %108, %109, %110, %111, %112, %113, %114, %115, %116, %117, %118, %119, %120, %121, %122, %123, %124, %125, %126, %127}, "
    "%128, %129, 1, 1, 1, 0, 1;\n"
    : "+f"(d[0]), "+f"(d[1]), "+f"(d[2]), "+f"(d[3]), "+f"(d[4]), "+f"(d[5]), "+f"(d[6]), "+f"(d[7]), "+f"(d[8]), "+f"(d[9]), "+f"(d[10]), "+f"(d[11]), "+f"(d[12]), "+f"(d[13]), "+f"(d[14]), "+f"(d[15]), "+f"(d[16]), "+f"(d[17]), "+f"(d[18]), "+f"(d[19]), "+f"(d[20]), "+f"(d[21]), "+f"(d[22]), "+f"(d[23]), "+f"(d[24]), "+f"(d[25]), "+f"(d[26]), "+f"(d[27]), "+f"(d[28]), "+f"(d[29]), "+f"(d[30]), "+f"(d[31]), "+f"(d[32]), "+f"(d[33]), "+f"(d[34]), "+f"(d[35]), "+f"(d[36]), "+f"(d[37]), "+f"(d[38]), "+f"(d[39]), "+f"(d[40]), "+f"(d[41]), "+f"(d[42]), "+f"(d[43]), "+f"(d[44]), "+f"(d[45]), "+f"(d[46]), "+f"(d[47]), "+f"(d[48]), "+f"(d[49]), "+f"(d[50]), "+f"(d[51]), "+f"(d[52]), "+f"(d[53]), "+f"(d[54]), "+f"(d[55]), "+f"(d[56]), "+f"(d[57]), "+f"(d[58]), "+f"(d[59]), "+f"(d[60]), "+f"(d[61]), "+f"(d[62]), "+f"(d[63]), "+f"(d[64]), "+f"(d[65]), "+f"(d[66]), "+f"(d[67]), "+f"(d[68]), "+f"(d[69]), "+f"(d[70]), "+f"(d[71]), "+f"(d[72]), "+f"(d[73]), "+f"(d[74]), "+f"(d[75]), "+f"(d[76]), "+f"(d[77]), "+f"(d[78]), "+f"(d[79]), "+f"(d[80]), "+f"(d[81]), "+f"(d[82]), "+f"(d[83]), "+f"(d[84]), "+f"(d[85]), "+f"(d[86]), "+f"(d[87]), "+f"(d[88]), "+f"(d[89]), "+f"(d[90]), "+f"(d[91]), "+f"(d[92]), "+f"(d[93]), "+f"(d[94]), "+f"(d[95]), "+f"(d[96]), "+f"(d[97]), "+f"(d[98]), "+f"(d[99]), "+f"(d[100]), "+f"(d[101]), "+f"(d[102]), "+f"(d[103]), "+f"(d[104]), "+f"(d[105]), "+f"(d[106]), "+f"(d[107]), "+f"(d[108]), "+f"(d[109]), "+f"(d[110]), "+f"(d[111]), "+f"(d[112]), "+f"(d[113]), "+f"(d[114]), "+f"(d[115]), "+f"(d[116]), "+f"(d[117]), "+f"(d[118]), "+f"(d[119]), "+f"(d[120]), "+f"(d[121]), "+f"(d[122]), "+f"(d[123]), "+f"(d[124]), "+f"(d[125]), "+f"(d[126]), "+f"(d[127])
    : "l"(da), "l"(db));
}

constexpr int kDim = 1024;
constexpr int kRows = 16384;
constexpr int kLayers = 6;
constexpr int kGroups = 32;
constexpr int kRounds = kRows / 128 / kGroups;
constexpr int kTiles = kRounds * kLayers;

constexpr int kJobs = kGroups;
constexpr int kEpoch = 32;
constexpr int NA = 4;
constexpr int NB = 8;
#define DCN_OFF 42.666668f
constexpr float kOffset = DCN_OFF;
#define DCN_KEEP 4
#define DCN_DRAIN 1
#define DCN_LAG 3
constexpr int DRAIN = DCN_DRAIN;
constexpr int LAG = DCN_LAG;
#define DCN_DUE 0
#define DCN_GQ 1
#define DCN_AS 0
#define DCN_CAD 460
#define DCN_NS0 0
#define DCN_NS1 128
constexpr int BPRE = 4;
constexpr int A_SLOT = 8192;
constexpr int B_SLOT = 16384;
constexpr int OFF_B = 0;
constexpr int OFF_A = OFF_B + NB * B_SLOT;
constexpr int NP = 3;
constexpr int OFF_P = OFF_A + 2 * NA * A_SLOT;
constexpr int OFF_UNIT = OFF_P + NP * A_SLOT;
constexpr int OFF_BIAS = OFF_UNIT + 2048;
constexpr int OFF_INIT = OFF_BIAS + kLayers * 256 * 2;
constexpr int OFF_BAR = OFF_INIT + 16;
constexpr int BAR_BFULL = OFF_BAR;
constexpr int BAR_BEMPTY = BAR_BFULL + NB * 8;
constexpr int BAR_AFULL = BAR_BEMPTY + NB * 8;
constexpr int BAR_AEMPTY = BAR_AFULL + 2 * NA * 8;
constexpr int BAR_XREADY = BAR_AEMPTY + 2 * NA * 8;
constexpr int BAR_PUB = BAR_XREADY + 16;
constexpr int BAR_PFULL = BAR_PUB + 16;
constexpr int BAR_PFREE = BAR_PFULL + 8 * 8;
constexpr int BAR_STAGED = BAR_PFREE + 8 * 8;
constexpr int BAR_ORDER = BAR_STAGED + 2 * NA * 8;
constexpr int BAR_BIAS = BAR_ORDER + 8;
constexpr int SMEM_BYTES = BAR_BIAS + 8;
static_assert(SMEM_BYTES <= 232448, "shared memory budget");

constexpr int kFlagSet = 4 * (kGroups + 1) * 2 * 32;
__device__ unsigned int g_flags[2 * kFlagSet];

__device__ __forceinline__ uint32_t smem_u32(const void* p) { return (uint32_t)__cvta_generic_to_shared(p); }
__device__ __forceinline__ void mbar_init(uint32_t bar, int cnt) {
  asm volatile("mbarrier.init.shared::cta.b64 [%0], %1;" ::"r"(bar), "r"(cnt) : "memory");
}
__device__ __forceinline__ void mbar_arrive(uint32_t bar) {
  asm volatile("mbarrier.arrive.shared::cta.b64 _, [%0];" ::"r"(bar) : "memory");
}
__device__ __forceinline__ uint32_t map_cta(uint32_t addr, uint32_t cta) {
  uint32_t r;
  asm volatile("mapa.shared::cluster.u32 %0, %1, %2;" : "=r"(r) : "r"(addr), "r"(cta));
  return r;
}
__device__ __forceinline__ void mbar_arrive_mapped(uint32_t cluster_addr) {
  asm volatile("mbarrier.arrive.shared::cluster.b64 _, [%0];" ::"r"(cluster_addr) : "memory");
}
__device__ __forceinline__ void mbar_arrive_mapped_if(uint32_t cluster_addr, bool pred) {
  asm volatile("{\n.reg .pred p;\nsetp.ne.u32 p, %1, 0;\n@p mbarrier.arrive.shared::cluster.b64 _, [%0];\n}"
               ::"r"(cluster_addr), "r"((uint32_t)pred) : "memory");
}
__device__ __forceinline__ void mbar_arrive_if(uint32_t bar, bool pred) {
  asm volatile("{\n.reg .pred p;\nsetp.ne.u32 p, %1, 0;\n@p mbarrier.arrive.shared::cta.b64 _, [%0];\n}"
               ::"r"(bar), "r"((uint32_t)pred) : "memory");
}
__device__ __forceinline__ void mbar_wait(uint32_t bar, uint32_t parity) {
  asm volatile(
      "{\n.reg .pred p;\n.reg .u32 c;\n"
      "mbarrier.try_wait.parity.shared::cta.b64 p, [%0], %1;\n"
      "@p bra DONE;\n"
      "mov.u32 c, 0;\n"
      "LOOP:\n"
      "mbarrier.try_wait.parity.shared::cta.b64 p, [%0], %1;\n"
      "@p bra DONE;\n"
      "add.u32 c, c, 1;\n"
      "setp.lt.u32 p, c, 4194304;\n"
      "@p bra LOOP;\n"
      "trap;\n"
      "DONE:\n}"
      ::"r"(bar), "r"(parity) : "memory");
}
__device__ __forceinline__ void mbar_spin(uint32_t bar, uint32_t parity) {
  asm volatile(
      "{\n.reg .pred p;\n"
      "LOOP:\n"
      "mbarrier.try_wait.parity.shared::cta.b64 p, [%0], %1;\n"
      "@!p bra LOOP;\n}"
      ::"r"(bar), "r"(parity) : "memory");
}
#define ELECT_BEGIN "{\n.reg .pred e;\nelect.sync _|e, 0xffffffff;\n"
template <bool STREAM> __device__ __forceinline__ void expect_load_2d_e(uint32_t dst, const CUtensorMap* m, uint32_t bar, int c0, int c1) {
  if (STREAM) {
    asm volatile(ELECT_BEGIN ".reg .b64 pol;\ncreatepolicy.fractional.L2::evict_first.b64 pol, 1.0;\n"
                 "@e mbarrier.arrive.expect_tx.shared::cta.b64 _, [%2], 8192;\n"
                 "@e cp.async.bulk.tensor.2d.shared::cluster.global.mbarrier::complete_tx::bytes.L2::cache_hint [%0], [%1, {%3, %4}], [%2], pol;\n}"
                 ::"r"(dst), "l"(m), "r"(bar), "r"(c0), "r"(c1) : "memory");
  } else {
    asm volatile(ELECT_BEGIN
                 "@e mbarrier.arrive.expect_tx.shared::cta.b64 _, [%2], 8192;\n"
                 "@e cp.async.bulk.tensor.2d.shared::cluster.global.mbarrier::complete_tx::bytes [%0], [%1, {%3, %4}], [%2];\n}"
                 ::"r"(dst), "l"(m), "r"(bar), "r"(c0), "r"(c1) : "memory");
  }
}
__device__ __forceinline__ void expect_load_2d_mc_e(uint32_t dst, const CUtensorMap* m, uint32_t bar, int c0, int c1) {
  asm volatile(ELECT_BEGIN ".reg .b64 pol;\ncreatepolicy.fractional.L2::evict_first.b64 pol, 1.0;\n"
               "@e mbarrier.arrive.expect_tx.shared::cta.b64 _, [%2], 8192;\n"
               "@e cp.async.bulk.tensor.2d.shared::cluster.global.mbarrier::complete_tx::bytes.multicast::cluster.L2::cache_hint [%0], [%1, {%3, %4}], [%2], %5, pol;\n}"
               ::"r"(dst), "l"(m), "r"(bar), "r"(c0), "r"(c1), "h"((uint16_t)3) : "memory");
}
__device__ __forceinline__ void expect_load_3d_e(uint32_t dst, const CUtensorMap* m, uint32_t bar, int c0, int c1, int c2) {
  asm volatile(ELECT_BEGIN
               "@e mbarrier.arrive.expect_tx.shared::cta.b64 _, [%2], 16384;\n"
               "@e cp.async.bulk.tensor.3d.shared::cluster.global.mbarrier::complete_tx::bytes [%0], [%1, {%3, %4, %5}], [%2];\n}"
               ::"r"(dst), "l"(m), "r"(bar), "r"(c0), "r"(c1), "r"(c2) : "memory");
}
template <bool STREAM> __device__ __forceinline__ void store_2d_e(const CUtensorMap* m, uint32_t src, int c0, int c1) {
  if (STREAM) {
    asm volatile(ELECT_BEGIN ".reg .b64 pol;\ncreatepolicy.fractional.L2::evict_first.b64 pol, 1.0;\n"
                 "@e cp.async.bulk.tensor.2d.global.shared::cta.bulk_group.L2::cache_hint [%0, {%2, %3}], [%1], pol;\n}"
                 ::"l"(m), "r"(src), "r"(c0), "r"(c1) : "memory");
  } else {
    asm volatile(ELECT_BEGIN
                 "@e cp.async.bulk.tensor.2d.global.shared::cta.bulk_group [%0, {%2, %3}], [%1];\n}"
                 ::"l"(m), "r"(src), "r"(c0), "r"(c1) : "memory");
  }
}
__device__ __forceinline__ void prefetch_2d_e(const CUtensorMap* m, int c0, int c1) {
  asm volatile(ELECT_BEGIN
               "@e cp.async.bulk.prefetch.tensor.2d.L2.global [%0, {%1, %2}];\n}"
               ::"l"(m), "r"(c0), "r"(c1) : "memory");
}
__device__ __forceinline__ void prefetch_1d_e(const void* ptr, uint32_t bytes) {
  asm volatile(ELECT_BEGIN
               "@e cp.async.bulk.prefetch.L2.global [%0], %1;\n}"
               ::"l"(ptr), "r"(bytes) : "memory");
}
__device__ __forceinline__ void grid_load_3d_e(uint32_t dst, const CUtensorMap* m, uint32_t bar, int c0, int c1, int c2) {
  asm volatile(ELECT_BEGIN
               ".reg .pred p;\n.reg .u32 a, b;\n.reg .u64 c;\n"
               "mov.u64 c, %%clock64;\ncvt.u32.u64 a, c;\n"
               "@e mbarrier.arrive.expect_tx.shared::cta.b64 _, [%2], 16384;\n"
               "EDGE:\n"
               "mov.u64 c, %%clock64;\ncvt.u32.u64 b, c;\n"
               "xor.b32 b, b, a;\n"
               "setp.lt.u32 p, b, 512;\n"
               "@p bra.uni EDGE;\n"
               "@e cp.async.bulk.tensor.3d.shared::cluster.global.mbarrier::complete_tx::bytes [%0], [%1, {%3, %4, %5}], [%2];\n}"
               ::"r"(dst), "l"(m), "r"(bar), "r"(c0), "r"(c1), "r"(c2) : "memory");
}
template <int NS> __device__ __forceinline__ void sleep_load_3d_e(uint32_t dst, const CUtensorMap* m, uint32_t bar, int c0, int c1, int c2) {
  asm volatile(ELECT_BEGIN
               "@e mbarrier.arrive.expect_tx.shared::cta.b64 _, [%2], 16384;\n"
               "nanosleep.u32 %6;\n"
               "@e cp.async.bulk.tensor.3d.shared::cluster.global.mbarrier::complete_tx::bytes [%0], [%1, {%3, %4, %5}], [%2];\n}"
               ::"r"(dst), "l"(m), "r"(bar), "r"(c0), "r"(c1), "r"(c2), "n"(NS) : "memory");
}
template <int NS> __device__ __forceinline__ void timed_load_3d_e(uint32_t dst, const CUtensorMap* m, uint32_t bar, int c0, int c1, int c2,
                                                                  uint32_t due, uint32_t& edge) {
  asm volatile(ELECT_BEGIN
               ".reg .pred p;\n.reg .s32 d;\n"
               "mov.u32 d, %%clock;\n"
               "@e mbarrier.arrive.expect_tx.shared::cta.b64 _, [%3], 16384;\n"
               "sub.s32 d, d, %0;\n"
               "setp.lt.u32 p, d, 200;\n"
               "@p bra.uni TEST;\n"
               "SLEEP:\n"
               "nanosleep.u32 %8;\n"
               "mov.u32 %0, %%clock;\n"
               "TEST:\n"
               "sub.s32 d, %0, %7;\n"
               "setp.lt.s32 p, d, 0;\n"
               "@p bra.uni SLEEP;\n"
               "@e cp.async.bulk.tensor.3d.shared::cluster.global.mbarrier::complete_tx::bytes [%1], [%2, {%4, %5, %6}], [%3];\n}"
               : "+r"(edge) : "r"(dst), "l"(m), "r"(bar), "r"(c0), "r"(c1), "r"(c2), "r"(due), "n"(NS) : "memory");
}
__device__ __forceinline__ void arrive_mapped_e(uint32_t cluster_addr) {
  asm volatile(ELECT_BEGIN "@e mbarrier.arrive.shared::cluster.b64 _, [%0];\n}" ::"r"(cluster_addr) : "memory");
}
__device__ __forceinline__ void arrive_e(uint32_t bar) {
  asm volatile(ELECT_BEGIN "@e mbarrier.arrive.shared::cta.b64 _, [%0];\n}" ::"r"(bar) : "memory");
}
__device__ __forceinline__ void bulk_commit() { asm volatile("cp.async.bulk.commit_group;" ::: "memory"); }
template <int N> __device__ __forceinline__ void bulk_wait() { asm volatile("cp.async.bulk.wait_group %0;" ::"n"(N) : "memory"); }
__device__ __forceinline__ void wg_fence() { asm volatile("wgmma.fence.sync.aligned;" ::: "memory"); }
__device__ __forceinline__ void wg_commit() { asm volatile("wgmma.commit_group.sync.aligned;" ::: "memory"); }
template <int N> __device__ __forceinline__ void wg_wait() { asm volatile("wgmma.wait_group.sync.aligned %0;" ::"n"(N) : "memory"); }
__device__ __forceinline__ void fence_async_global() { asm volatile("fence.proxy.async.global;" ::: "memory"); }
__device__ __forceinline__ void st_relaxed(unsigned int* p, unsigned int v) {
  asm volatile("st.relaxed.gpu.global.u32 [%0], %1;" ::"l"(p), "r"(v) : "memory");
}
__device__ __forceinline__ unsigned int ld_acquire(const unsigned int* p) {
  unsigned int v;
  asm volatile("ld.acquire.gpu.global.u32 %0, [%1];" : "=r"(v) : "l"(p) : "memory");
  return v;
}
__device__ __forceinline__ void ldsm4(uint32_t* r, uint32_t addr) {
  asm volatile("ldmatrix.sync.aligned.m8n8.x4.shared.b16 {%0, %1, %2, %3}, [%4];"
               : "=r"(r[0]), "=r"(r[1]), "=r"(r[2]), "=r"(r[3]) : "r"(addr) : "memory");
}
__device__ __forceinline__ void stsm4(uint32_t addr, const uint32_t* r) {
  asm volatile("stmatrix.sync.aligned.m8n8.x4.shared.b16 [%0], {%1, %2, %3, %4};"
               ::"r"(addr), "r"(r[0]), "r"(r[1]), "r"(r[2]), "r"(r[3]) : "memory");
}
template <bool V> struct Flag { static constexpr bool value = V; };
__device__ __forceinline__ void fence_async_smem() { asm volatile("fence.proxy.async.shared::cta;" ::: "memory"); }
__device__ __forceinline__ void cluster_arrive_relaxed() { asm volatile("barrier.cluster.arrive.relaxed.aligned;" ::: "memory"); }
__device__ __forceinline__ void cluster_wait() { asm volatile("barrier.cluster.wait.acquire.aligned;" ::: "memory"); }
__device__ __forceinline__ void prefetch_map(const CUtensorMap* m) {
  asm volatile("prefetch.tensormap [%0];" ::"l"(m) : "memory");
}
__device__ __forceinline__ void poll_flag(const unsigned int* ptr, unsigned int target) {
  asm volatile(
      "{\n.reg .pred p;\n.reg .u32 c;\n.reg .s32 v;\n"
      "mov.u32 c, 0;\n"
      "LOOP:\n"
      "ld.acquire.gpu.global.s32 v, [%0];\n"
      "sub.s32 v, v, %1;\n"
      "setp.ge.s32 p, v, 0;\n"
      "@p bra DONE;\n"
      "add.u32 c, c, 1;\n"
      "setp.lt.u32 p, c, 4194304;\n"
      "@p bra LOOP;\n"
      "trap;\n"
      "DONE:\n}"
      ::"l"(ptr), "r"(target) : "memory");
}

constexpr uint32_t DESC_HI = (1024u >> 4) | (1u << 30);
__device__ __forceinline__ uint64_t desc(uint32_t lo) { return ((uint64_t)DESC_HI << 32) | lo; }
constexpr uint32_t DESC_A_LBO = 1u << 16;
constexpr uint32_t DESC_B_LBO = (4096u >> 4) << 16;

__host__ __device__ constexpr int bempty_off(int slot) { return ((slot & 1) ? 0 : 32) + (slot >> 1) * 8; }

__device__ __forceinline__ int kgroup_col(int j, int q) {
  return q == 0 ? j : (q == 1 ? (j ^ 1) : (((j ^ 2) & ~1) + (q - 2)));
}

__device__ __forceinline__ int role_of_cluster(int c) {
  const int a = c - 4;
  const int b = c - 36, r = (b * 37) >> 8;
  const int first = (a & ~7) + (a & 3) * 2 + ((a >> 2) & 1);
  const int second = 32 + r * 8 + ((0x7531640 >> (((b - r * 7) * 4) & 31)) & 7);
  return c >= 2 * kGroups ? c : (c >= 36 ? second : (c >= 4 ? first : 34 + c * 8));
}
__device__ __forceinline__ int helped_round(int grp) { return (grp & 2) ? (grp & 3) - 1 : 3; }
__device__ __forceinline__ int job_of_group(int grp) {
  return (grp & 2) ? (grp & 1) * 8 + (grp >> 2) : 16 + (grp >> 2) * 2 + (grp & 1);
}
__device__ __forceinline__ int job_row(int n) {
  const int grp = n < 16 ? (n & 7) * 4 + 2 + (n >> 3) : ((n - 16) >> 1) * 4 + (n & 1);
  return (helped_round(grp) * kGroups + grp) * 128;
}

#define PROF_ENDS(idx) do {} while (0)
#define PROF_SVC(idx) do {} while (0)
#define PROF_SKEW(idx) do {} while (0)
#define PROF(idx) do {} while (0)
#define PROF_DUMP() do {} while (0)
constexpr int PROF_SMEM = 0;

__global__ void __cluster_dims__(2, 1, 1) __launch_bounds__(384, 1)
dcn_kernel(const __grid_constant__ CUtensorMap mx64, const __grid_constant__ CUtensorMap mx32,
           const __grid_constant__ CUtensorMap mo64, const __grid_constant__ CUtensorMap mo32,
           const __grid_constant__ CUtensorMap mw, const __grid_constant__ CUtensorMap mp,
           const __nv_bfloat16* __restrict__ xptr,
           const __nv_bfloat16* __restrict__ wptr, const __nv_bfloat16* __restrict__ bias, __nv_bfloat16* optr) {
  extern __shared__ __align__(1024) uint8_t smem_raw[];
  const uint32_t sb = smem_u32(smem_raw);
  const int tid = threadIdx.x;
  if (tid == 256) {
    prefetch_map(&mw);
    prefetch_map(&mx64);
    mbar_init(sb + BAR_BFULL, 1);
    mbar_init(sb + BAR_BFULL + 8, 1);
    mbar_init(sb + BAR_AFULL, 1);
    mbar_init(sb + BAR_AFULL + NA * 8, 1);
    asm volatile("fence.mbarrier_init.release.cluster;" ::: "memory");
  }
  const int wg = __shfl_sync(0xffffffffu, tid >> 7, 0);
  const int warp = __shfl_sync(0xffffffffu, (tid >> 5) & 3, 0);
  const int bid = role_of_cluster(blockIdx.x >> 1) * 2 + (blockIdx.x & 1);
  const int j = bid & 3;
  const int grp = bid >> 2;
  const uint32_t rank = j & 1;
  const bool helper = grp == kGroups;
  const int short_t = (gridDim.x > 4 * kGroups && !helper) ? helped_round(grp) * kLayers : -1;
  if (tid == 0) PROF_ENDS(1000);

  const int col0 = helper ? kgroup_col(j, 2) * 256 : 0;
  const int row0 = helper ? job_row(0) : grp * 128;
  if (tid < 32 && !helper) {
    asm volatile("prefetch.global.L2 [%0];" ::"l"(wptr + (size_t)((grp & 7) * 8 + (tid >> 2)) * kDim + j * 256 + (tid & 3) * 64));
    asm volatile("prefetch.global.L2 [%0];" ::"l"(xptr + (size_t)(row0 + j * 32 + tid) * kDim));
  }
  auto first_loads = [&](int s) {
    const int col = col0 + s * 64;
    expect_load_3d_e(sb + OFF_B + 2 * s * B_SLOT, &mw, sb + BAR_BFULL + 2 * s * 8, 0, col, j * 4);
    expect_load_2d_e<false>(sb + OFF_A + s * A_SLOT, &mx64, sb + BAR_AFULL + s * 8, col, row0);
    expect_load_3d_e(sb + OFF_B + (2 * s + 1) * B_SLOT, &mw, sb + BAR_BFULL + (2 * s + 1) * 8, 0, col + 32, j * 4);
    expect_load_2d_e<false>(sb + OFF_A + (NA + s) * A_SLOT, &mx64, sb + BAR_AFULL + (NA + s) * 8, col, row0 + 64);
  };
  if (wg == 2 && warp == 0) first_loads(0);
  if (tid == 288) {
    if (sb & 1023) asm volatile("trap;");
#pragma unroll
    for (int i = 0; i < NB; i++) mbar_init(sb + BAR_BEMPTY + i * 8, 2);
#pragma unroll
    for (int i = 0; i < 2 * NA; i++) { mbar_init(sb + BAR_AEMPTY + i * 8, 2); mbar_init(sb + BAR_STAGED + i * 8, 4); }
    asm volatile("fence.mbarrier_init.release.cluster;" ::: "memory");
  }
  if (tid == 352) {
#pragma unroll
    for (int i = 0; i < 8; i++) { mbar_init(sb + BAR_PFULL + i * 8, 1); mbar_init(sb + BAR_PFREE + i * 8, 1); }
    asm volatile("fence.mbarrier_init.release.cluster;" ::: "memory");
  }
  if (tid == 320) {
#pragma unroll
    for (int i = 2; i < NB; i++) mbar_init(sb + BAR_BFULL + i * 8, 1);
#pragma unroll
    for (int i = 0; i < 2 * NA; i++)
      if (i % NA) mbar_init(sb + BAR_AFULL + i * 8, 1);
#pragma unroll
    for (int i = 0; i < 4; i++) mbar_init(sb + BAR_XREADY + i * 8, 1);
    mbar_init(sb + BAR_ORDER, 1);
    mbar_init(sb + BAR_BIAS, 32);
    asm volatile("st.shared.v4.f32 [%0], {%1, %1, %1, %1};" ::"r"(sb + OFF_INIT), "f"(kOffset) : "memory");
    asm volatile("fence.mbarrier_init.release.cluster;" ::: "memory");
  }
  __syncthreads();
  cluster_arrive_relaxed();

  if (wg == 2) {
    asm volatile("setmaxnreg.dec.sync.aligned.u32 40;");
    if (warp == 0) {
#pragma unroll 1
      for (int s = 1; s < 4; s++) first_loads(s);
      cluster_wait();
      uint32_t par = 0, due, edge = 0;
      asm volatile("mov.u32 %0, %%clock;" : "=r"(due));
      int l = 0;
      const int ntiles = helper ? kJobs : kTiles;
#pragma unroll 1
      for (int t = 0; t < ntiles; t++) {
        const int jo = (t == 0 && !helper) ? 0 : j;
        const int q_end = t == short_t ? 2 : 4;
#pragma unroll 1
        for (int q = (helper ? 2 : 0) + (t == 0); q < q_end; q++) {
          const int krow = l * kDim + kgroup_col(jo, q) * 256;
          if (q < DCN_GQ || helper || (q == 1 && (t == short_t || t == 0))) {
#pragma unroll
            for (int i = 0; i < NB; i++) {
              mbar_spin(sb + BAR_BEMPTY + bempty_off(i), par);
              expect_load_3d_e(sb + OFF_B + i * B_SLOT, &mw, sb + BAR_BFULL + i * 8, 0, krow + i * 32, j * 4);
              if (i == 5 && q == 0) { asm volatile("mov.u32 %0, %%clock;" : "=r"(due)); due += DCN_DUE; }
              PROF_SKEW(t * 32 + q * 8 + i);
            }
          } else {
#pragma unroll
            for (int i = 0; i < NB; i++) {
              mbar_spin(sb + BAR_BEMPTY + bempty_off(i), par);
              sleep_load_3d_e<DCN_NS1>(sb + OFF_B + i * B_SLOT, &mw, sb + BAR_BFULL + i * 8, 0, krow + i * 32, j * 4);
              PROF_SKEW(t * 32 + q * 8 + i);
            }
          }
          par ^= 1;
        }
        if (helper || ++l == kLayers) l = 0;
      }
    } else if (warp <= 2) {
      const int w = warp - 1;
      const uint32_t abase = sb + OFF_A + w * NA * A_SLOT;
      const uint32_t fullb = sb + BAR_AFULL + w * NA * 8;
      const uint32_t emptyb = sb + BAR_AEMPTY + w * NA * 8;
      const uint32_t stagedb = sb + BAR_STAGED + w * NA * 8;
      const unsigned int base = __shfl_sync(0xffffffffu, *(volatile unsigned int*)(g_flags + (bid * 2 + w) * 32), 0);
      cluster_wait();
      uint32_t epar = 0;
      uint32_t spar = 0;
      auto refill = [&](const CUtensorMap* m, int col, int row) {
#pragma unroll 1
        for (int s = 0; s < 4; s++) {
          mbar_wait(emptyb + s * 8, epar);
          expect_load_2d_e<false>(abase + s * A_SLOT, m, fullb + s * 8, col + s * 64, row);
        }
        epar ^= 1;
      };
      auto store_refill = [&](int out_row, int col, int row, bool last_read) {
#pragma unroll 1
        for (int s = 0; s < 4; s++) {
          mbar_wait(stagedb + s * 8, spar);
          fence_async_smem();
          store_2d_e<true>(&mo64, abase + s * A_SLOT, j * 256 + s * 64, out_row);
          bulk_commit();
          bulk_wait<0>();
          __syncwarp();
          mbar_wait(emptyb + s * 8, epar);
          if (last_read) expect_load_2d_e<true>(abase + s * A_SLOT, &mx64, fullb + s * 8, col + s * 64, row);
          else expect_load_2d_e<false>(abase + s * A_SLOT, &mx64, fullb + s * 8, col + s * 64, row);
        }
        spar ^= 1;
        epar ^= 1;
      };
      auto store_tile = [&](auto stream, int out_row) {
#pragma unroll 1
        for (int c = 0; c < 4; c++) {
          mbar_wait(stagedb + c * 8, spar);
          fence_async_smem();
          store_2d_e<decltype(stream)::value>(&mo64, abase + c * A_SLOT, j * 256 + c * 64, out_row);
        }
        spar ^= 1;
        bulk_commit();
        bulk_wait<0>();
        __syncwarp();
      };
      auto refill_shared = [&](const CUtensorMap* m32, int col, int row) {
#pragma unroll 1
        for (int s = 0; s < 4; s++) {
          mbar_wait(emptyb + s * 8, epar);
          expect_load_2d_mc_e(abase + s * A_SLOT + rank * 4096, m32, fullb + s * 8, col + s * 64, row + rank * 32);
        }
        epar ^= 1;
      };
      if (helper) {
#pragma unroll 1
        for (int h = 1; h < 2 * kJobs; h++) refill_shared(&mx32, col0 + (h & 1) * 256, job_row(h >> 1) + w * 64);
      } else {
        const uint32_t xready_peer = map_cta(sb + BAR_XREADY + w * 8, rank ^ 1);
        const unsigned int* oflag = g_flags + ((grp * 4 + kgroup_col(j, 2)) * 2 + w) * 32;
        unsigned int* done_mine = g_flags + kFlagSet + (bid * 2 + w) * 32;
        const unsigned int* done_peer = g_flags + kFlagSet + ((bid ^ 2) * 2 + w) * 32;
        uint32_t nx = 0;
        uint32_t fpar = 0;
#pragma unroll 1
        for (int rd = 0; rd < kRounds; rd++) {
          const int xrow = (rd * kGroups + grp) * 128 + w * 64;
          if (rd == 0) {
            refill(&mx64, 256, xrow);
          } else {
            poll_flag(done_peer, base + nx);
            store_refill(xrow - kGroups * 128, (j ^ 1) * 256, xrow, rd * kLayers == short_t);
          }
          if (rd * kLayers != short_t) {
#pragma unroll 1
            for (int h = 0; h < 2; h++) refill_shared(&mx32, (kgroup_col(rd == 0 ? 0 : j, 2) + h) * 256, xrow);
          }
          fpar ^= 1;
#pragma unroll 1
          for (int l = 1; l < kLayers; l++) {
            if (l > 1) poll_flag(done_peer, base + nx);
            store_tile(Flag<false>(), xrow);
            PROF_SVC((rd * kLayers + l - 1) * 2 + w);
            arrive_mapped_e(xready_peer);
            arrive_e(sb + BAR_PUB + w * 8);
            mbar_wait(sb + BAR_XREADY + w * 8, nx & 1);
            fence_async_global();
            refill(&mo64, (j ^ 1) * 256, xrow);
#pragma unroll 1
            for (int h = 0; h < 2; h++) {
              poll_flag(oflag + h * 64, base + nx + 1);
              fence_async_global();
              refill_shared(&mo32, (kgroup_col(j, 2) + h) * 256, xrow);
            }
            fpar ^= 1;
            if (rank) {
#pragma unroll 1
              for (int s = 0; s < 4; s++) mbar_wait(fullb + s * 8, fpar);
            }
            nx++;
            if ((tid & 31) == 0) st_relaxed(done_mine, base + (nx == kRounds * (kLayers - 1) ? kEpoch : nx));
            __syncwarp();
          }
          const int nrow = xrow + kGroups * 128;
          if (rd + 1 == kRounds) {
            poll_flag(done_peer, base + nx);
            store_tile(Flag<true>(), xrow);
          } else {
            refill(&mx64, j * 256, nrow);
            fpar ^= 1;
          }
          PROF_SVC((rd * kLayers + kLayers - 1) * 2 + w);
        }
      }
    } else {
      const int lane = tid & 31;
      unsigned int* myflag = g_flags + bid * 2 * 32;
      if (lane == 0) { prefetch_map(&mx32); prefetch_map(&mo64); prefetch_map(&mo32); }
      const unsigned int base = *(volatile unsigned int*)myflag;
      auto publish = [&](uint32_t n, uint32_t value) {
#pragma unroll 1
        for (int w = 0; w < 2; w++) {
          mbar_wait(sb + BAR_PUB + w * 8, n & 1);
          asm volatile("fence.acq_rel.gpu;" ::: "memory");
          if (lane == 0) st_relaxed(myflag + w * 32, base + value);
          __syncwarp();
        }
      };
      if (helper) {
        cluster_wait();
#pragma unroll 1
        for (int n = 0; n < kJobs; n++) {
          if (n + 2 < kJobs) {
            const int row = job_row(n + 2);
#pragma unroll 1
            for (int i = 0; i < 8; i++) prefetch_2d_e(&mx64, col0 + rank * 256 + (i & 3) * 64, row + (i >> 2) * 64);
          }
          publish(n, n + 1);
        }
      } else {
        {
          float c[8];
#pragma unroll
          for (int i = 0; i < 8; i++) c[i] = 0.f;
#pragma unroll 1
          for (int l = 0; l < kLayers; l++) {
            const uint4 v = *reinterpret_cast<const uint4*>(bias + l * kDim + j * 256 + lane * 8);
            const uint32_t u[4] = {v.x, v.y, v.z, v.w};
#pragma unroll
            for (int i = 0; i < 4; i++) {
              c[2 * i] += __uint_as_float(u[i] << 16);
              c[2 * i + 1] += __uint_as_float(u[i] & 0xffff0000u);
              uint32_t pk;
              asm("cvt.rn.bf16x2.f32 %0, %1, %2;" : "=r"(pk) : "f"(c[2 * i + 1]), "f"(c[2 * i]));
              asm volatile("st.shared.u32 [%0], %1;" ::"r"(sb + OFF_BIAS + l * 512 + (lane >> 2) * 64 + i * 16 + (lane & 3) * 4),
                           "r"(pk) : "memory");
            }
          }
#pragma unroll
          for (int i = 0; i < 15; i++) {
            const uint32_t one = (lane >> 3) == (lane & 3) ? 0x3f80u << ((lane & 4) * 4) : 0u;
            asm volatile("st.shared.u32 [%0], %1;" ::"r"(sb + OFF_UNIT + i * 128 + lane * 4), "r"(i == 7 ? one : 0u) : "memory");
          }
          fence_async_smem();
          mbar_arrive(sb + BAR_BIAS);
        }
        const __nv_bfloat16* wslice = wptr + bid * 8192;
        prefetch_1d_e(wslice + kDim * kDim, 16384);
        cluster_wait();
        uint32_t nx = 0;
#pragma unroll 1
        for (int rd = 0; rd < kRounds; rd++) {
#pragma unroll 1
          for (int l = 1; l < kLayers; l++) {
            publish(nx, nx + 1 == kRounds * (kLayers - 1) ? kEpoch : nx + 1);
            nx++;
            if (l < kLayers - 1) {
              if (rd == 0) prefetch_1d_e(wslice + (l + 1) * kDim * kDim, 16384);
            } else if (rd + 1 < kRounds) {
              const int nrow = ((rd + 1) * kGroups + grp) * 128;
#pragma unroll 1
              for (int i = 0; i < 8; i++) {
                prefetch_2d_e(&mx64, j * 256 + (i >> 1) * 64, nrow + (i & 1) * 64);
                __nanosleep(300);
              }
              if ((rd + 1) * kLayers == short_t) {
                poll_flag(g_flags + ((4 * kGroups + j) * 2 + 1) * 32, base + job_of_group(grp) + 1);
                fence_async_global();
                constexpr uint32_t order = 0x76325140;
#pragma unroll 1
                for (int i = NP; i < 8; i++)
                  prefetch_2d_e(&mp, j * 256 + ((order >> (i * 4)) & 3) * 64, nrow + ((order >> (i * 4)) & 4) * 16);
#pragma unroll 1
                for (int i = 0; i < 8; i++) {
                  if (i >= NP) mbar_wait(sb + BAR_PFREE + (i - NP) * 8, 0);
                  PROF(776 + i);
                  expect_load_2d_e<true>(sb + OFF_P + (i % NP) * A_SLOT, &mp, sb + BAR_PFULL + i * 8,
                                         j * 256 + ((order >> (i * 4)) & 3) * 64, nrow + ((order >> (i * 4)) & 4) * 16);
                }
              }
            }
          }
        }
      }
    }
    if (warp == (helper ? 3 : 2) && (tid & 31) == 0) PROF_ENDS(1002);
    if (warp == 2) PROF_DUMP();
  } else {
    asm volatile("setmaxnreg.inc.sync.aligned.u32 232;");
    const int lane = tid & 31;
    const int wtid = tid & 127;
    const uint32_t abase = sb + OFF_A + wg * NA * A_SLOT;
    const uint32_t afull = sb + BAR_AFULL + wg * NA * 8;
    const uint32_t rel = map_cta(sb + (wtid == 64 ? BAR_BEMPTY : BAR_AEMPTY + wg * NA * 8), wtid == 32 ? (rank ^ 1) : rank);
    const bool rel_b = wtid == 64;
    const bool rel_ab = (wtid & 31) == 0 && wtid < 96;
    const uint32_t frag0 = __shfl_sync(0xffffffffu, abase + ((wtid >> 5) * 16 + ((lane >> 3) & 1) * 8 + (lane & 7)) * 128 +
                                                        (((lane >> 4) ^ (lane & 7)) << 4), lane);
    const uint64_t adesc0 = desc(((abase & 0x3FFFF) >> 4) | DESC_A_LBO);
    const uint64_t bdesc0 = desc((((sb + OFF_B) & 0x3FFFF) >> 4) | DESC_B_LBO);

    const uint64_t zero = gridDim.y - 1;
    uint64_t adesc_q = adesc0 + zero, bdesc_q = bdesc0 + zero;

    float acc[128];
    uint32_t xr[64];
#pragma unroll
    for (int i = 0; i < 128; i++) acc[i] = kOffset;
#pragma unroll
    for (int i = 0; i < 64; i++) xr[i] = 0;
    uint32_t bpar = 0;
    uint32_t fpar = 0;
    int l = 0;
    bool hold = false;
    bool swap = false;
    bool brief = helper;
    int capture_q = helper ? -1 : j;

    auto release = [&](int i, bool with_a) {
      mbar_arrive_mapped_if(rel + bempty_off(i), (i & 1) ? with_a : rel_b);
    };
    auto chunk_staged = [&](int c) {
      __syncwarp();
      arrive_e(sb + BAR_STAGED + (wg * NA + c) * 8);
    };
    auto capture_slot = [&](int p) {
#pragma unroll
      for (int g = 0; g < 4; g++) ldsm4(&xr[(p * 4 + g) * 4], (frag0 ^ (g * 32)) + p * A_SLOT);
    };
    auto swap_half = [&](int p, int half) {
#pragma unroll
      for (int g = half * 2; g < half * 2 + 2; g++) {
        const uint32_t addr = (frag0 ^ (g * 32)) + p * A_SLOT;
        uint32_t n[4];
        ldsm4(n, addr);
        stsm4(addr, &xr[(p * 4 + g) * 4]);
#pragma unroll
        for (int i = 0; i < 4; i++) xr[(p * 4 + g) * 4 + i] = n[i];
      }
      if (half) chunk_staged(p);
    };
    auto chunk_of = [&](int c) { return wg ? (0x7631 >> (c * 4)) & 7 : (0x5420 >> (c * 4)) & 7; };
    auto add_partial = [&](int c) __attribute__((always_inline)) {
      const int n = chunk_of(c);
      const int slot = wg ? (0x1001 >> (c * 4)) & 3 : (0x2120 >> (c * 4)) & 3;
      PROF(768 + wg * 16 + c * 2);
      mbar_spin(sb + BAR_PFULL + n * 8, 0);
      PROF(768 + wg * 16 + c * 2 + 1);
      wg_fence();
      wgmma_n256(acc, ((uint64_t)(128 >> 4) << 32) | ((128 >> 4) << 16) | (((sb + OFF_UNIT + (6 - 2 * c) * 128) & 0x3FFFF) >> 4),
                 ((uint64_t)(256 >> 4) << 32) | ((128 >> 4) << 16) | (((sb + OFF_P + slot * A_SLOT) & 0x3FFFF) >> 4));
    };
    auto issue = [&](int i, bool wait_a, bool wait_b) __attribute__((always_inline)) {
      if (wait_a && !(i & 1)) mbar_spin(afull + (i >> 1) * 8, fpar);
      if (wait_b) mbar_spin(sb + BAR_BFULL + i * 8, bpar);
      const uint64_t adesc = (i < NB - DCN_KEEP ? adesc_q : adesc0) + ((i >> 1) * (A_SLOT >> 4) + (i & 1) * 4);
      const uint64_t bdesc = (i < NB - DCN_KEEP ? bdesc_q : bdesc0) + i * (B_SLOT >> 4);
      wg_fence();
      wgmma_n256(acc, adesc, bdesc);
      wgmma_n256(acc, adesc + 2, bdesc + 128);
      wg_commit();
      if (i == NB - 1) { adesc_q += zero; bdesc_q += zero; }
    };
    auto retire = [&](int i, bool with_a) {
      wg_wait<2>();
      release((i + 6) & 7, with_a);
    };
    auto k_loop = [&](auto first, int t) __attribute__((always_inline)) {
      constexpr bool FIRST = decltype(first)::value;
      const bool inject = FIRST && brief && !helper;
      auto extras = [&](int q, int i, bool swap_now) __attribute__((always_inline)) {
        if (!FIRST) return;
        if (swap_now) swap_half(((i + 5) >> 1) & 3, (i + 1) & 1);
        if ((i & 1) && q == capture_q) capture_slot(i >> 1);
      };
      auto free_partial = [&](int c) {
        if (FIRST) mbar_arrive_if(sb + BAR_PFREE + chunk_of(c) * 8, inject && rel_b);
      };
#pragma unroll
      for (int i = 1; i < 8; i++) {
        if (!(i & 1)) PROF(t * 32 + wg * 16 + 8 + (i >> 1));
        if ((i == 1 || i == 7) && inject) add_partial(i >> 2);
        issue(i, FIRST, true);
        if (i >= 2) retire(i, rel_ab);
        if (i == 3) free_partial(0);
        extras(0, i, i >= 3 && swap);
      }
      bpar ^= 1;
      if (FIRST) fpar ^= 1;
      PROF(t * 32 + wg * 16 + 1);
      if (!FIRST || !brief) {
#pragma unroll 1
        for (int q = 1; q < 3; q++) {
#pragma unroll
          for (int i = 0; i < 8; i++) {
            issue(i, true, true);
            if (i == 0) PROF(t * 32 + wg * 16 + 3 + q);
            retire(i, rel_ab);
            extras(q, i, i < 3 && swap);
          }
          bpar ^= 1;
          fpar ^= 1;
          if (FIRST) swap = false;
        }
      }
      const bool rel_last = hold ? rel_ab : rel_b;
#pragma unroll
      for (int i = 0; i < DRAIN; i++) {
        issue(i, true, true);
        retire(i, rel_ab);
        extras(3, i, swap);
      }
      if (wg == 1) {
        wg_wait<1>();
        release((DRAIN + 6) & 7, rel_ab);
        wg_wait<0>();
        release((DRAIN + 7) & 7, rel_ab);
        free_partial(1);
        PROF(t * 32 + wg * 16 + 12);
#pragma unroll
        for (int i = DRAIN; i < 3; i++) extras(-2, i, swap);
        mbar_spin(sb + BAR_ORDER, t & 1);
        PROF(t * 32 + wg * 16 + 6);
#pragma unroll
        for (int i = DRAIN; i < 3; i++) {
          issue(i, true, true);
          if (i >= DRAIN + 2) retire(i, rel_ab);
          extras(3, i, false);
        }
      } else {
        PROF(t * 32 + wg * 16 + 6);
#pragma unroll
        for (int i = DRAIN; i < 3; i++) {
          issue(i, true, true);
          retire(i, rel_ab);
          if (i == 1) free_partial(1);
          extras(3, i, swap);
        }
      }
#pragma unroll
      for (int i = 3; i < 8; i++) {
        if ((i == 3 || i == 6) && inject) add_partial(i == 3 ? 2 : 3);
        issue(i, true, true);
        if (i == 7 && tid == 96) mbar_arrive(sb + BAR_ORDER);
        retire(i, rel_last);
        if (i == 5) free_partial(2);
        extras(3, i, false);
      }
      bpar ^= 1;
      fpar ^= 1;
    };

    cluster_wait();
    const int ntiles = helper ? kJobs : kTiles;
    issue(0, true, true);
#pragma unroll 1
    for (int t = 0;; t++) {
      hold = (helper || l == kLayers - 1) && (t + 1 < ntiles);
      PROF(t * 32 + wg * 16 + 0);
      if (l == 0) k_loop(Flag<true>(), t);
      else k_loop(Flag<false>(), t);
      if (t == 0 && !helper) mbar_spin(sb + BAR_BIAS, 0);
      const uint32_t bl = sb + OFF_BIAS + l * 512 + (lane & 3) * 16;
      uint32_t bq[8][4];
      auto load_bias = [&](int U) {
        asm volatile("ld.shared.v4.u32 {%0, %1, %2, %3}, [%4];"
                     : "=r"(bq[U][0]), "=r"(bq[U][1]), "=r"(bq[U][2]), "=r"(bq[U][3]) : "r"(bl + U * 64));
      };
#pragma unroll
      for (int U = 0; U < BPRE; U++) load_bias(U);
      uint32_t fa[4];
#pragma unroll
      for (int g = 0; g < 4; g++) asm volatile("xor.b32 %0, %1, %2;" : "=r"(fa[g]) : "r"(frag0), "r"(g * 32));
      wg_wait<1>();
      release(6, false);
      wg_wait<0>();
#pragma unroll
      for (int i = 0; i < 128; i++) asm volatile("" : "+f"(acc[i]) :: "memory");
      release(7, hold ? rel_ab : rel_b);
      PROF(t * 32 + wg * 16 + 2);

      auto pack = [&](int i, float off) {
        uint32_t v;
        asm("cvt.rn.bf16x2.f32 %0, %1, %2;" : "=r"(v) : "f"(acc[i * 2 + 1] - off), "f"(acc[i * 2] - off));
        return v;
      };
      auto cross = [&](int T, int i, float off) {
        uint32_t s2 = pack(T * 4 + i, off), o;
        asm("add.rn.bf16x2 %0, %1, %2;" : "=r"(s2) : "r"(s2), "r"(bq[T >> 1][(T & 1) * 2 + (i >> 1)]));
        asm("fma.rn.bf16x2 %0, %1, %2, %1;" : "=r"(o) : "r"(xr[T * 4 + i]), "r"(s2));
        return o;
      };
      auto reset = [&](int T) {
#pragma unroll
        for (int i = T * 8; i < T * 8 + 8; i += 4)
          asm volatile("ld.volatile.shared.v4.f32 {%0, %1, %2, %3}, [%4];"
                       : "+f"(acc[i]), "+f"(acc[i + 1]), "+f"(acc[i + 2]), "+f"(acc[i + 3]) : "r"(sb + OFF_INIT));
      };
      auto offset_for = [&](int T) { return T >= LAG ? acc[(T - LAG) * 8 + 7] : kOffset; };
      if (helper) {
        __nv_bfloat16* dst = optr + (size_t)(job_row(t) + wg * 64) * kDim + j * 256 + (wtid >> 5) * 64 + lane * 2;
        uint64_t pol;
        asm volatile("createpolicy.fractional.L2::evict_first.b64 %0, 1.0;" : "=l"(pol));
#pragma unroll
        for (int T = 0; T < 16; T++) {
#pragma unroll
          for (int i = 0; i < 4; i++)
            asm volatile("st.global.L2::cache_hint.b32 [%0], %1, %2;"
                         ::"l"(dst + (T * 4 + (i ^ 1)) * kDim), "r"(pack(T * 4 + i, offset_for(T))), "l"(pol) : "memory");
          reset(T);
        }
        asm volatile("bar.sync %0, 128;" ::"r"(wg + 1) : "memory");
        if (wtid == 0) mbar_arrive(sb + BAR_PUB + wg * 8);
      } else if (hold) {
#pragma unroll
        for (int T = 0; T < 16; T++) {
#pragma unroll
          for (int i = 0; i < 4; i++) xr[T * 4 + i] = cross(T, i, offset_for(T));
          if ((T & 1) && (T >> 1) + BPRE < 8) load_bias((T >> 1) + BPRE);
          reset(T);
        }
      } else {
#pragma unroll
        for (int T = 0; T < 16; T++) {
          uint32_t o[4];
#pragma unroll
          for (int i = 0; i < 4; i++) o[i] = cross(T, i, kOffset);
          stsm4(fa[T & 3] + (T >> 2) * A_SLOT, o);
          if ((T & 3) == 3) chunk_staged(T >> 2);
          if ((T & 1) && (T >> 1) + BPRE < 8) load_bias((T >> 1) + BPRE);
        }
        PROF(t * 32 + wg * 16 + 7);
        fence_async_smem();
        asm volatile("bar.sync %0, 128;" ::"r"(wg + 1) : "memory");
      }
      PROF(t * 32 + wg * 16 + 3);
      if (t + 1 == ntiles) break;
      issue(0, hold, true);
      if (helper || ++l == kLayers) l = 0;
      swap = hold && !helper;
      brief = helper || t + 1 == short_t;
      capture_q = -1;
    }
  }
}

__global__ void __launch_bounds__(256) dcn_fallback(const __nv_bfloat16* __restrict__ x0, const __nv_bfloat16* __restrict__ w,
                                                    const __nv_bfloat16* __restrict__ b, __nv_bfloat16* __restrict__ out) {
  __shared__ float xs[8][kDim];
  const size_t r0 = (size_t)blockIdx.x * 8;
  for (int i = threadIdx.x; i < 8 * kDim; i += 256) xs[i / kDim][i % kDim] = __bfloat162float(x0[r0 * kDim + i]);
  __syncthreads();
  for (int l = 0; l < kLayers; l++) {
    float a[4][8] = {};
    for (int k = 0; k < kDim; k++) {
#pragma unroll
      for (int c = 0; c < 4; c++) {
        const float wv = __bfloat162float(w[((size_t)l * kDim + k) * kDim + c * 256 + threadIdx.x]);
#pragma unroll
        for (int r = 0; r < 8; r++) a[c][r] += xs[r][k] * wv;
      }
    }
    __syncthreads();
#pragma unroll
    for (int c = 0; c < 4; c++) {
      const int n = c * 256 + threadIdx.x;
#pragma unroll
      for (int r = 0; r < 8; r++) {
        const float v = __bfloat162float(x0[(r0 + r) * kDim + n]) * (a[c][r] + __bfloat162float(b[l * kDim + n])) + xs[r][n];
        xs[r][n] = __bfloat162float(__float2bfloat16(v));
      }
    }
    __syncthreads();
  }
  for (int i = threadIdx.x; i < 8 * kDim; i += 256) out[r0 * kDim + i] = __float2bfloat16(xs[i / kDim][i % kDim]);
}

typedef CUresult (*EncodeFn)(CUtensorMap*, CUtensorMapDataType, cuuint32_t, void*, const cuuint64_t*, const cuuint64_t*,
                             const cuuint32_t*, const cuuint32_t*, CUtensorMapInterleave, CUtensorMapSwizzle,
                             CUtensorMapL2promotion, CUtensorMapFloatOOBfill);

static void make_map_2d(EncodeFn enc, CUtensorMap* m, void* ptr, uint64_t rows, uint32_t box_rows,
                        CUtensorMapSwizzle swizzle = CU_TENSOR_MAP_SWIZZLE_128B) {
  cuuint64_t dims[2] = {(cuuint64_t)kDim, rows};
  cuuint64_t strides[1] = {kDim * 2};
  cuuint32_t box[2] = {64, box_rows};
  cuuint32_t es[2] = {1, 1};
  enc(m, CU_TENSOR_MAP_DATA_TYPE_BFLOAT16, 2, ptr, dims, strides, box, es, CU_TENSOR_MAP_INTERLEAVE_NONE,
      swizzle, CU_TENSOR_MAP_L2_PROMOTION_L2_128B, CU_TENSOR_MAP_FLOAT_OOB_FILL_NONE);
}

}

extern "C" void kernel_launch(void* const* d_in, const int* in_sizes, int n_in, void* d_out, int out_size) {
  using namespace dcn;
  (void)in_sizes; (void)n_in; (void)out_size;
  void* fn = nullptr;
  cudaDriverEntryPointQueryResult qr;
  cudaGetDriverEntryPoint("cuTensorMapEncodeTiled", &fn, cudaEnableDefault, &qr);
  EncodeFn enc = (EncodeFn)fn;
  CUtensorMap mx64, mx32, mo64, mo32, mw, mp;
  make_map_2d(enc, &mx64, d_in[0], kRows, 64);
  make_map_2d(enc, &mx32, d_in[0], kRows, 32);
  make_map_2d(enc, &mo64, d_out, kRows, 64);
  make_map_2d(enc, &mo32, d_out, kRows, 32);
  make_map_2d(enc, &mp, d_out, kRows, 64, CU_TENSOR_MAP_SWIZZLE_NONE);
  {
    cuuint64_t dims[3] = {64, (cuuint64_t)kLayers * kDim, kDim / 64};
    cuuint64_t strides[2] = {kDim * 2, 128};
    cuuint32_t box[3] = {64, 32, 4};
    cuuint32_t es[3] = {1, 1, 1};
    enc(&mw, CU_TENSOR_MAP_DATA_TYPE_BFLOAT16, 3, d_in[1], dims, strides, box, es, CU_TENSOR_MAP_INTERLEAVE_NONE,
        CU_TENSOR_MAP_SWIZZLE_128B, CU_TENSOR_MAP_L2_PROMOTION_L2_128B, CU_TENSOR_MAP_FLOAT_OOB_FILL_NONE);
  }
  const __nv_bfloat16* x0 = (const __nv_bfloat16*)d_in[0];
  const __nv_bfloat16* w = (const __nv_bfloat16*)d_in[1];
  const __nv_bfloat16* b = (const __nv_bfloat16*)d_in[2];
  __nv_bfloat16* out = (__nv_bfloat16*)d_out;
  constexpr int smem = SMEM_BYTES + PROF_SMEM;
  cudaFuncSetAttribute(dcn_kernel, cudaFuncAttributeMaxDynamicSharedMemorySize, smem);

  cudaLaunchConfig_t cfg = {};
  cfg.gridDim = dim3(4 * kGroups + 4);
  cfg.blockDim = dim3(384);
  cfg.dynamicSmemBytes = smem;
  cudaLaunchAttribute attr;
  attr.id = cudaLaunchAttributeClusterDimension;
  attr.val.clusterDim.x = 2;
  attr.val.clusterDim.y = 1;
  attr.val.clusterDim.z = 1;
  cfg.attrs = &attr;
  cfg.numAttrs = 1;
  int clusters = 0;
  cudaOccupancyMaxActiveClusters(&clusters, dcn_kernel, &cfg);
  if (clusters >= 2 * kGroups) {
    const int grid = 4 * kGroups + (clusters >= 2 * kGroups + 2 ? 4 : 0);
    dcn_kernel<<<grid, 384, smem>>>(mx64, mx32, mo64, mo32, mw, mp, x0, w, b, out);
  } else {
    dcn_fallback<<<kRows / 8, 256>>>(x0, w, b, out);
  }
}
```

```cpp
#include <cuda_runtime.h>
#include <cuda.h>
#include <cuda_bf16.h>
#include <stdint.h>

namespace dcn {

__device__ __forceinline__ void wgmma_n256(float (&d)[128], uint64_t da, uint64_t db) {
  asm volatile("wgmma.mma_async.sync.aligned.m64n256k16.f32.bf16.bf16 "
    "{%0, %1, %2, %3, %4, %5, %6, %7, %8, %9, %10, %11, %12, %13, %14, %15, %16, %17, %18, %19, %20, %21, %22, %23, %24, %25, %26, %27, %28, %29, %30, %31, %32, %33, %34, %35, %36, %37, %38, %39, %40, %41, %42, %43, %44, %45, %46, %47, %48, %49, %50, %51, %52, %53, %54, %55, %56, %57, %58, %59, %60, %61, %62, %63, %64, %65, %66, %67, %68, %69, %70, %71, %72, %73, %74, %75, %76, %77, %78, %79, %80, %81, %82, %83, %84, %85, %86, %87, %88, %89, %90, %91, %92, %93, %94, %95, %96, %97, %98, %99, %100, %101, %102, %103, %104, %105, %106, %107, %108, %109, %110, %111, %112, %113, %114, %115, %116, %117, %118, %119, %120, %121, %122, %123, %124, %125, %126, %127}, "
    "%128, %129, 1, 1, 1, 0, 1;\n"
    : "+f"(d[0]), "+f"(d[1]), "+f"(d[2]), "+f"(d[3]), "+f"(d[4]), "+f"(d[5]), "+f"(d[6]), "+f"(d[7]), "+f"(d[8]), "+f"(d[9]), "+f"(d[10]), "+f"(d[11]), "+f"(d[12]), "+f"(d[13]), "+f"(d[14]), "+f"(d[15]), "+f"(d[16]), "+f"(d[17]), "+f"(d[18]), "+f"(d[19]), "+f"(d[20]), "+f"(d[21]), "+f"(d[22]), "+f"(d[23]), "+f"(d[24]), "+f"(d[25]), "+f"(d[26]), "+f"(d[27]), "+f"(d[28]), "+f"(d[29]), "+f"(d[30]), "+f"(d[31]), "+f"(d[32]), "+f"(d[33]), "+f"(d[34]), "+f"(d[35]), "+f"(d[36]), "+f"(d[37]), "+f"(d[38]), "+f"(d[39]), "+f"(d[40]), "+f"(d[41]), "+f"(d[42]), "+f"(d[43]), "+f"(d[44]), "+f"(d[45]), "+f"(d[46]), "+f"(d[47]), "+f"(d[48]), "+f"(d[49]), "+f"(d[50]), "+f"(d[51]), "+f"(d[52]), "+f"(d[53]), "+f"(d[54]), "+f"(d[55]), "+f"(d[56]), "+f"(d[57]), "+f"(d[58]), "+f"(d[59]), "+f"(d[60]), "+f"(d[61]), "+f"(d[62]), "+f"(d[63]), "+f"(d[64]), "+f"(d[65]), "+f"(d[66]), "+f"(d[67]), "+f"(d[68]), "+f"(d[69]), "+f"(d[70]), "+f"(d[71]), "+f"(d[72]), "+f"(d[73]), "+f"(d[74]), "+f"(d[75]), "+f"(d[76]), "+f"(d[77]), "+f"(d[78]), "+f"(d[79]), "+f"(d[80]), "+f"(d[81]), "+f"(d[82]), "+f"(d[83]), "+f"(d[84]), "+f"(d[85]), "+f"(d[86]), "+f"(d[87]), "+f"(d[88]), "+f"(d[89]), "+f"(d[90]), "+f"(d[91]), "+f"(d[92]), "+f"(d[93]), "+f"(d[94]), "+f"(d[95]), "+f"(d[96]), "+f"(d[97]), "+f"(d[98]), "+f"(d[99]), "+f"(d[100]), "+f"(d[101]), "+f"(d[102]), "+f"(d[103]), "+f"(d[104]), "+f"(d[105]), "+f"(d[106]), "+f"(d[107]), "+f"(d[108]), "+f"(d[109]), "+f"(d[110]), "+f"(d[111]), "+f"(d[112]), "+f"(d[113]), "+f"(d[114]), "+f"(d[115]), "+f"(d[116]), "+f"(d[117]), "+f"(d[118]), "+f"(d[119]), "+f"(d[120]), "+f"(d[121]), "+f"(d[122]), "+f"(d[123]), "+f"(d[124]), "+f"(d[125]), "+f"(d[126]), "+f"(d[127])
    : "l"(da), "l"(db));
}

constexpr int kDim = 1024;
constexpr int kRows = 16384;
constexpr int kLayers = 6;
constexpr int kGroups = 32;
constexpr int kRounds = kRows / 128 / kGroups;
constexpr int kTiles = kRounds * kLayers;

constexpr int kJobs = kGroups;
constexpr int kEpoch = 32;
constexpr int NA = 4;
constexpr int NB = 8;
#define DCN_OFF 42.666668f
constexpr float kOffset = DCN_OFF;
#define DCN_DRAIN 1
#define DCN_LAG 3
constexpr int DRAIN = DCN_DRAIN;
constexpr int LAG = DCN_LAG;
#define DCN_AS 0
#define DCN_ORD 7
#define DCN_BPRE 4
#define DCN_ELAG 0
constexpr int BPRE = DCN_BPRE;
constexpr int A_SLOT = 8192;
constexpr int B_SLOT = 16384;
constexpr int OFF_B = 0;
constexpr int NP = 3;
constexpr int OFF_P = OFF_B + NB * B_SLOT;
constexpr int OFF_A = OFF_P + NP * A_SLOT;
constexpr int OFF_UNIT = OFF_A + 2 * NA * A_SLOT;
constexpr int OFF_BIAS = OFF_UNIT + 2048;
constexpr int OFF_INIT = OFF_BIAS + kLayers * 256 * 2;
constexpr int OFF_BAR = OFF_INIT + 16;
constexpr int BAR_BFULL = OFF_BAR;
constexpr int BAR_BFULL0 = BAR_BFULL + NB * 8;
constexpr int BAR_BEMPTY = BAR_BFULL0 + 8;
constexpr int BAR_AFULL = BAR_BEMPTY + NB * 8;
constexpr int BAR_AEMPTY = BAR_AFULL + 2 * NA * 8;
constexpr int BAR_XREADY = BAR_AEMPTY + 2 * NA * 8;
constexpr int BAR_PUB = BAR_XREADY + 16;
constexpr int BAR_PFULL = BAR_PUB + 16;
constexpr int BAR_PFREE = BAR_PFULL + 8 * 8;
constexpr int BAR_STAGED = BAR_PFREE + 8 * 8;
constexpr int BAR_ORDER = BAR_STAGED + 2 * NA * 8;
constexpr int BAR_BIAS = BAR_ORDER + 8;
constexpr int SMEM_BYTES = BAR_BIAS + 8;
static_assert(SMEM_BYTES <= 232448, "shared memory budget");

constexpr int kFlagSet = 4 * (kGroups + 1) * 2 * 32;
__device__ unsigned int g_flags[2 * kFlagSet];

__device__ __forceinline__ uint32_t smem_u32(const void* p) { return (uint32_t)__cvta_generic_to_shared(p); }
__device__ __forceinline__ void mbar_init(uint32_t bar, int cnt) {
  asm volatile("mbarrier.init.shared::cta.b64 [%0], %1;" ::"r"(bar), "r"(cnt) : "memory");
}
__device__ __forceinline__ void mbar_arrive(uint32_t bar) {
  asm volatile("mbarrier.arrive.shared::cta.b64 _, [%0];" ::"r"(bar) : "memory");
}
__device__ __forceinline__ uint32_t map_cta(uint32_t addr, uint32_t cta) {
  uint32_t r;
  asm volatile("mapa.shared::cluster.u32 %0, %1, %2;" : "=r"(r) : "r"(addr), "r"(cta));
  return r;
}
__device__ __forceinline__ void mbar_arrive_mapped(uint32_t cluster_addr) {
  asm volatile("mbarrier.arrive.shared::cluster.b64 _, [%0];" ::"r"(cluster_addr) : "memory");
}
__device__ __forceinline__ void mbar_arrive_mapped_if(uint32_t cluster_addr, bool pred) {
  asm volatile("{\n.reg .pred p;\nsetp.ne.u32 p, %1, 0;\n@p mbarrier.arrive.shared::cluster.b64 _, [%0];\n}"
               ::"r"(cluster_addr), "r"((uint32_t)pred) : "memory");
}
__device__ __forceinline__ void mbar_arrive_if(uint32_t bar, bool pred) {
  asm volatile("{\n.reg .pred p;\nsetp.ne.u32 p, %1, 0;\n@p mbarrier.arrive.shared::cta.b64 _, [%0];\n}"
               ::"r"(bar), "r"((uint32_t)pred) : "memory");
}
__device__ __forceinline__ void mbar_wait(uint32_t bar, uint32_t parity) {
  asm volatile(
      "{\n.reg .pred p;\n.reg .u32 c;\n"
      "mbarrier.try_wait.parity.shared::cta.b64 p, [%0], %1;\n"
      "@p bra DONE;\n"
      "mov.u32 c, 0;\n"
      "LOOP:\n"
      "mbarrier.try_wait.parity.shared::cta.b64 p, [%0], %1;\n"
      "@p bra DONE;\n"
      "add.u32 c, c, 1;\n"
      "setp.lt.u32 p, c, 4194304;\n"
      "@p bra LOOP;\n"
      "trap;\n"
      "DONE:\n}"
      ::"r"(bar), "r"(parity) : "memory");
}
__device__ __forceinline__ void mbar_spin(uint32_t bar, uint32_t parity) {
  asm volatile(
      "{\n.reg .pred p;\n"
      "LOOP:\n"
      "mbarrier.try_wait.parity.shared::cta.b64 p, [%0], %1;\n"
      "@!p bra LOOP;\n}"
      ::"r"(bar), "r"(parity) : "memory");
}
#define ELECT_BEGIN "{\n.reg .pred e;\nelect.sync _|e, 0xffffffff;\n"
template <bool STREAM> __device__ __forceinline__ void expect_load_2d_e(uint32_t dst, const CUtensorMap* m, uint32_t bar, int c0, int c1) {
  if (STREAM) {
    asm volatile(ELECT_BEGIN ".reg .b64 pol;\ncreatepolicy.fractional.L2::evict_first.b64 pol, 1.0;\n"
                 "@e mbarrier.arrive.expect_tx.shared::cta.b64 _, [%2], 8192;\n"
                 "@e cp.async.bulk.tensor.2d.shared::cluster.global.mbarrier::complete_tx::bytes.L2::cache_hint [%0], [%1, {%3, %4}], [%2], pol;\n}"
                 ::"r"(dst), "l"(m), "r"(bar), "r"(c0), "r"(c1) : "memory");
  } else {
    asm volatile(ELECT_BEGIN
                 "@e mbarrier.arrive.expect_tx.shared::cta.b64 _, [%2], 8192;\n"
                 "@e cp.async.bulk.tensor.2d.shared::cluster.global.mbarrier::complete_tx::bytes [%0], [%1, {%3, %4}], [%2];\n}"
                 ::"r"(dst), "l"(m), "r"(bar), "r"(c0), "r"(c1) : "memory");
  }
}
__device__ __forceinline__ void expect_load_2d_mc_e(uint32_t dst, const CUtensorMap* m, uint32_t bar, int c0, int c1) {
  asm volatile(ELECT_BEGIN ".reg .b64 pol;\ncreatepolicy.fractional.L2::evict_first.b64 pol, 1.0;\n"
               "@e mbarrier.arrive.expect_tx.shared::cta.b64 _, [%2], 8192;\n"
               "@e cp.async.bulk.tensor.2d.shared::cluster.global.mbarrier::complete_tx::bytes.multicast::cluster.L2::cache_hint [%0], [%1, {%3, %4}], [%2], %5, pol;\n}"
               ::"r"(dst), "l"(m), "r"(bar), "r"(c0), "r"(c1), "h"((uint16_t)3) : "memory");
}
__device__ __forceinline__ void expect_load_3d_e(uint32_t dst, const CUtensorMap* m, uint32_t bar, int c0, int c1, int c2) {
  asm volatile(ELECT_BEGIN
               "@e mbarrier.arrive.expect_tx.shared::cta.b64 _, [%2], 16384;\n"
               "@e cp.async.bulk.tensor.3d.shared::cluster.global.mbarrier::complete_tx::bytes [%0], [%1, {%3, %4, %5}], [%2];\n}"
               ::"r"(dst), "l"(m), "r"(bar), "r"(c0), "r"(c1), "r"(c2) : "memory");
}
template <bool STREAM> __device__ __forceinline__ void store_2d_e(const CUtensorMap* m, uint32_t src, int c0, int c1) {
  if (STREAM) {
    asm volatile(ELECT_BEGIN ".reg .b64 pol;\ncreatepolicy.fractional.L2::evict_first.b64 pol, 1.0;\n"
                 "@e cp.async.bulk.tensor.2d.global.shared::cta.bulk_group.L2::cache_hint [%0, {%2, %3}], [%1], pol;\n}"
                 ::"l"(m), "r"(src), "r"(c0), "r"(c1) : "memory");
  } else {
    asm volatile(ELECT_BEGIN
                 "@e cp.async.bulk.tensor.2d.global.shared::cta.bulk_group [%0, {%2, %3}], [%1];\n}"
                 ::"l"(m), "r"(src), "r"(c0), "r"(c1) : "memory");
  }
}
__device__ __forceinline__ void prefetch_2d_e(const CUtensorMap* m, int c0, int c1) {
  asm volatile(ELECT_BEGIN
               "@e cp.async.bulk.prefetch.tensor.2d.L2.global [%0, {%1, %2}];\n}"
               ::"l"(m), "r"(c0), "r"(c1) : "memory");
}
__device__ __forceinline__ void prefetch_1d_e(const void* ptr, uint32_t bytes) {
  asm volatile(ELECT_BEGIN
               "@e cp.async.bulk.prefetch.L2.global [%0], %1;\n}"
               ::"l"(ptr), "r"(bytes) : "memory");
}
__device__ __forceinline__ void paced_load_3d_e(uint32_t dst, const CUtensorMap* m, uint32_t bar, int c0, int c1, int c2) {
  asm volatile(ELECT_BEGIN
               "@e mbarrier.arrive.expect_tx.shared::cta.b64 _, [%2], 16384;\n"
               "nanosleep.u32 128;\n"
               "@e cp.async.bulk.tensor.3d.shared::cluster.global.mbarrier::complete_tx::bytes [%0], [%1, {%3, %4, %5}], [%2];\n}"
               ::"r"(dst), "l"(m), "r"(bar), "r"(c0), "r"(c1), "r"(c2) : "memory");
}
__device__ __forceinline__ void arrive_mapped_e(uint32_t cluster_addr) {
  asm volatile(ELECT_BEGIN "@e mbarrier.arrive.shared::cluster.b64 _, [%0];\n}" ::"r"(cluster_addr) : "memory");
}
__device__ __forceinline__ void arrive_e(uint32_t bar) {
  asm volatile(ELECT_BEGIN "@e mbarrier.arrive.shared::cta.b64 _, [%0];\n}" ::"r"(bar) : "memory");
}
__device__ __forceinline__ void bulk_commit() { asm volatile("cp.async.bulk.commit_group;" ::: "memory"); }
template <int N> __device__ __forceinline__ void bulk_wait() { asm volatile("cp.async.bulk.wait_group %0;" ::"n"(N) : "memory"); }
__device__ __forceinline__ void wg_fence() { asm volatile("wgmma.fence.sync.aligned;" ::: "memory"); }
__device__ __forceinline__ void wg_commit() { asm volatile("wgmma.commit_group.sync.aligned;" ::: "memory"); }
template <int N> __device__ __forceinline__ void wg_wait() { asm volatile("wgmma.wait_group.sync.aligned %0;" ::"n"(N) : "memory"); }
__device__ __forceinline__ void fence_async_global() { asm volatile("fence.proxy.async.global;" ::: "memory"); }
__device__ __forceinline__ void st_relaxed(unsigned int* p, unsigned int v) {
  asm volatile("st.relaxed.gpu.global.u32 [%0], %1;" ::"l"(p), "r"(v) : "memory");
}
__device__ __forceinline__ unsigned int ld_acquire(const unsigned int* p) {
  unsigned int v;
  asm volatile("ld.acquire.gpu.global.u32 %0, [%1];" : "=r"(v) : "l"(p) : "memory");
  return v;
}
__device__ __forceinline__ void ldsm4(uint32_t* r, uint32_t addr) {
  asm volatile("ldmatrix.sync.aligned.m8n8.x4.shared.b16 {%0, %1, %2, %3}, [%4];"
               : "=r"(r[0]), "=r"(r[1]), "=r"(r[2]), "=r"(r[3]) : "r"(addr) : "memory");
}
__device__ __forceinline__ void stsm4(uint32_t addr, const uint32_t* r) {
  asm volatile("stmatrix.sync.aligned.m8n8.x4.shared.b16 [%0], {%1, %2, %3, %4};"
               ::"r"(addr), "r"(r[0]), "r"(r[1]), "r"(r[2]), "r"(r[3]) : "memory");
}
template <bool V> struct Flag { static constexpr bool value = V; };
__device__ __forceinline__ void fence_async_smem() { asm volatile("fence.proxy.async.shared::cta;" ::: "memory"); }
__device__ __forceinline__ void cluster_arrive_relaxed() { asm volatile("barrier.cluster.arrive.relaxed.aligned;" ::: "memory"); }
__device__ __forceinline__ void cluster_wait() { asm volatile("barrier.cluster.wait.acquire.aligned;" ::: "memory"); }
__device__ __forceinline__ void prefetch_map(const CUtensorMap* m) {
  asm volatile("prefetch.tensormap [%0];" ::"l"(m) : "memory");
}
__device__ __forceinline__ void poll_flag(const unsigned int* ptr, unsigned int target) {
  asm volatile(
      "{\n.reg .pred p;\n.reg .u32 c;\n.reg .s32 v;\n"
      "mov.u32 c, 0;\n"
      "LOOP:\n"
      "ld.acquire.gpu.global.s32 v, [%0];\n"
      "sub.s32 v, v, %1;\n"
      "setp.ge.s32 p, v, 0;\n"
      "@p bra DONE;\n"
      "add.u32 c, c, 1;\n"
      "setp.lt.u32 p, c, 4194304;\n"
      "@p bra LOOP;\n"
      "trap;\n"
      "DONE:\n}"
      ::"l"(ptr), "r"(target) : "memory");
}

constexpr uint32_t DESC_HI = (1024u >> 4) | (1u << 30);
__device__ __forceinline__ uint64_t desc(uint32_t lo) { return ((uint64_t)DESC_HI << 32) | lo; }
constexpr uint32_t DESC_A_LBO = 1u << 16;
constexpr uint32_t DESC_B_LBO = (4096u >> 4) << 16;

__host__ __device__ constexpr int bempty_off(int slot) { return ((slot & 1) ? 0 : 32) + (slot >> 1) * 8; }

__device__ __forceinline__ int kgroup_col(int j, int q) {
  return q == 0 ? j : (q == 1 ? (j ^ 1) : (((j ^ 2) & ~1) + (q - 2)));
}

__device__ __forceinline__ int role_of_cluster(int c) {
  const int a = c - 4;
  const int b = c - 36, r = (b * 37) >> 8;
  const int first = (a & ~7) + (a & 3) * 2 + ((a >> 2) & 1);
  const int second = 32 + r * 8 + ((0x7531640 >> (((b - r * 7) * 4) & 31)) & 7);
  return c >= 2 * kGroups ? c : (c >= 36 ? second : (c >= 4 ? first : 34 + c * 8));
}
__device__ __forceinline__ int helped_round(int grp) { return (grp & 2) ? (grp & 3) - 1 : 3; }
__device__ __forceinline__ int job_of_group(int grp) {
  return (grp & 2) ? (grp & 1) * 8 + (grp >> 2) : 16 + (grp >> 2) * 2 + (grp & 1);
}
__device__ __forceinline__ int job_row(int n) {
  const int grp = n < 16 ? (n & 7) * 4 + 2 + (n >> 3) : ((n - 16) >> 1) * 4 + (n & 1);
  return (helped_round(grp) * kGroups + grp) * 128;
}

#define PROF_ENDS(idx) do {} while (0)
#define PROF_SVC(idx) do {} while (0)
#define PROF_SKEW(idx) do {} while (0)
#define PROF(idx) do {} while (0)
#define PROF_DUMP() do {} while (0)
constexpr int PROF_SMEM = 0;

__global__ void __cluster_dims__(2, 1, 1) __launch_bounds__(384, 1)
dcn_kernel(const __grid_constant__ CUtensorMap mx64, const __grid_constant__ CUtensorMap mx32,
           const __grid_constant__ CUtensorMap mo64, const __grid_constant__ CUtensorMap mo32,
           const __grid_constant__ CUtensorMap mw, const __grid_constant__ CUtensorMap mp,
           const __nv_bfloat16* __restrict__ xptr,
           const __nv_bfloat16* __restrict__ wptr, const __nv_bfloat16* __restrict__ bias, __nv_bfloat16* optr) {
  extern __shared__ __align__(1024) uint8_t smem_raw[];
  const uint32_t sb = smem_u32(smem_raw);
  const int tid = threadIdx.x;
  if (tid == 256) {
    prefetch_map(&mw);
    prefetch_map(&mx64);
    mbar_init(sb + BAR_BFULL0, 1);
    mbar_init(sb + BAR_BFULL + 8, 1);
    mbar_init(sb + BAR_AFULL, 1);
    mbar_init(sb + BAR_AFULL + NA * 8, 1);
    asm volatile("fence.mbarrier_init.release.cluster;" ::: "memory");
  }
  const int wg = __shfl_sync(0xffffffffu, tid >> 7, 0);
  const int warp = __shfl_sync(0xffffffffu, (tid >> 5) & 3, 0);
  const int bid = role_of_cluster(blockIdx.x >> 1) * 2 + (blockIdx.x & 1);
  const int j = bid & 3;
  const int grp = bid >> 2;
  const uint32_t rank = j & 1;
  const bool helper = grp == kGroups;
  const int short_t = (gridDim.x > 4 * kGroups && !helper) ? helped_round(grp) * kLayers : -8;
  const unsigned lend = helper ? ~0u : 1u;
  auto moves_up = [&](int t) { return (unsigned)(t + 1 - short_t) > lend; };
  if (tid == 0) PROF_ENDS(1000);

  const int col0 = helper ? kgroup_col(j, 2) * 256 : 0;
  const int row0 = helper ? job_row(0) : grp * 128;
  if (tid < 32 && !helper) {
    asm volatile("prefetch.global.L2 [%0];" ::"l"(wptr + (size_t)((grp & 7) * 8 + (tid >> 2)) * kDim + j * 256 + (tid & 3) * 64));
    asm volatile("prefetch.global.L2 [%0];" ::"l"(xptr + (size_t)(row0 + j * 32 + tid) * kDim));
  }
  auto first_loads = [&](int s) {
    const int col = col0 + s * 64;
    expect_load_3d_e(sb + OFF_B + 2 * s * B_SLOT, &mw, sb + (s ? BAR_BFULL + 2 * s * 8 : BAR_BFULL0), 0, col, j * 4);
    expect_load_2d_e<false>(sb + OFF_A + s * A_SLOT, &mx64, sb + BAR_AFULL + s * 8, col, row0);
    expect_load_3d_e(sb + OFF_B + (2 * s + 1) * B_SLOT, &mw, sb + BAR_BFULL + (2 * s + 1) * 8, 0, col + 32, j * 4);
    expect_load_2d_e<false>(sb + OFF_A + (NA + s) * A_SLOT, &mx64, sb + BAR_AFULL + (NA + s) * 8, col, row0 + 64);
  };
  if (wg == 2 && warp == 0) first_loads(0);
  if (tid == 288) {
    if (sb & 1023) asm volatile("trap;");
#pragma unroll
    for (int i = 0; i < NB; i++) mbar_init(sb + BAR_BEMPTY + i * 8, 2);
#pragma unroll
    for (int i = 0; i < 2 * NA; i++) { mbar_init(sb + BAR_AEMPTY + i * 8, 2); mbar_init(sb + BAR_STAGED + i * 8, 4); }
    asm volatile("fence.mbarrier_init.release.cluster;" ::: "memory");
  }
  if (tid == 352) {
#pragma unroll
    for (int i = 0; i < 8; i++) { mbar_init(sb + BAR_PFULL + i * 8, 1); mbar_init(sb + BAR_PFREE + i * 8, 1); }
    asm volatile("fence.mbarrier_init.release.cluster;" ::: "memory");
  }
  if (tid == 320) {
#pragma unroll
    for (int i = 0; i < NB; i++)
      if (i != 1) mbar_init(sb + BAR_BFULL + i * 8, 1);
#pragma unroll
    for (int i = 0; i < 2 * NA; i++)
      if (i % NA) mbar_init(sb + BAR_AFULL + i * 8, 1);
#pragma unroll
    for (int i = 0; i < 4; i++) mbar_init(sb + BAR_XREADY + i * 8, 1);
    mbar_init(sb + BAR_ORDER, 1);
    mbar_init(sb + BAR_BIAS, 32);
    asm volatile("st.shared.v4.f32 [%0], {%1, %1, %1, %1};" ::"r"(sb + OFF_INIT), "f"(kOffset) : "memory");
    asm volatile("fence.mbarrier_init.release.cluster;" ::: "memory");
  }
  __syncthreads();
  cluster_arrive_relaxed();

  if (wg == 2) {
    asm volatile("setmaxnreg.dec.sync.aligned.u32 40;");
    if (warp == 0) {
#pragma unroll 1
      for (int s = 1; s < 4; s++) first_loads(s);
      cluster_wait();
      uint32_t par = 0;
      int l = 0;
      const int ntiles = helper ? kJobs : kTiles;
#pragma unroll 1
      for (int t = 0; t < ntiles; t++) {
        const int jo = (t == 0 && !helper) ? 0 : j;
        const int q_end = t == short_t ? 2 : 4;
#pragma unroll 1
        for (int q = (helper ? 2 : 0) + (t == 0); q < q_end; q++) {
          const int krow = l * kDim + kgroup_col(jo, q) * 256;
          if (q == (helper ? 2 : 0)) {
            const bool early = moves_up(t - 1);
#pragma unroll
            for (int i = 0; i < NB; i++) {
              if (i > 0 || !early) mbar_spin(sb + BAR_BEMPTY + (early && i > 0 ? bempty_off(i - 1) : bempty_off(i)), par);
              if (i <= DRAIN && early) __nanosleep(128);
              expect_load_3d_e(sb + OFF_B + i * B_SLOT, &mw, sb + (i ? BAR_BFULL + i * 8 : BAR_BFULL0), 0, krow + i * 32, j * 4);
              PROF_SKEW(t * 32 + q * 8 + i);
            }
          } else {
            const bool up = q >= 2 && moves_up(t);
            const bool late = up && q == 2;
            const uint32_t dst = sb + OFF_B + (up ? B_SLOT : 0);
            if (helper || (q == 1 && (t == short_t || t == 0))) {
#pragma unroll 1
              for (int i = 0; i < NB; i++) {
                mbar_spin(sb + BAR_BEMPTY + bempty_off(i), par);
                expect_load_3d_e(dst + i * B_SLOT, &mw, sb + BAR_BFULL + i * 8, 0, krow + i * 32, j * 4);
                PROF_SKEW(t * 32 + q * 8 + i);
              }
            } else {
#pragma unroll
              for (int i = 0; i < NB; i++) {
                mbar_spin(sb + BAR_BEMPTY + (late && i < 7 ? bempty_off(i + 1) : bempty_off(i)), par);
                paced_load_3d_e(dst + i * B_SLOT, &mw, sb + BAR_BFULL + i * 8, 0, krow + i * 32, j * 4);
                PROF_SKEW(t * 32 + q * 8 + i);
              }
            }
          }
          par ^= 1;
        }
        if (helper || ++l == kLayers) l = 0;
      }
    } else if (warp <= 2) {
      const int w = warp - 1;
      const uint32_t abase = sb + OFF_A + w * NA * A_SLOT;
      const uint32_t fullb = sb + BAR_AFULL + w * NA * 8;
      const uint32_t emptyb = sb + BAR_AEMPTY + w * NA * 8;
      const uint32_t stagedb = sb + BAR_STAGED + w * NA * 8;
      const unsigned int base = __shfl_sync(0xffffffffu, *(volatile unsigned int*)(g_flags + (bid * 2 + w) * 32), 0);
      cluster_wait();
      uint32_t epar = 0;
      uint32_t spar = 0;
      auto refill = [&](const CUtensorMap* m, int col, int row) {
#pragma unroll 1
        for (int s = 0; s < 4; s++) {
          mbar_wait(emptyb + s * 8, epar);
          expect_load_2d_e<false>(abase + s * A_SLOT, m, fullb + s * 8, col + s * 64, row);
        }
        epar ^= 1;
      };
      auto store_refill = [&](int out_row, int col, int row, bool last_read) {
#pragma unroll 1
        for (int s = 0; s < 4; s++) {
          mbar_wait(stagedb + s * 8, spar);
          fence_async_smem();
          store_2d_e<true>(&mo64, abase + s * A_SLOT, j * 256 + s * 64, out_row);
          bulk_commit();
          bulk_wait<0>();
          __syncwarp();
          mbar_wait(emptyb + s * 8, epar);
          if (last_read) expect_load_2d_e<true>(abase + s * A_SLOT, &mx64, fullb + s * 8, col + s * 64, row);
          else expect_load_2d_e<false>(abase + s * A_SLOT, &mx64, fullb + s * 8, col + s * 64, row);
        }
        spar ^= 1;
        epar ^= 1;
      };
      auto store_tile = [&](auto stream, int out_row) {
#pragma unroll 1
        for (int c = 0; c < 4; c++) {
          mbar_wait(stagedb + c * 8, spar);
          fence_async_smem();
          arrive_e(fullb + c * 8);
          store_2d_e<decltype(stream)::value>(&mo64, abase + c * A_SLOT, j * 256 + c * 64, out_row);
        }
        spar ^= 1;
        bulk_commit();
        bulk_wait<0>();
        __syncwarp();
      };
      auto refill_shared = [&](const CUtensorMap* m32, int col, int row) {
#pragma unroll 1
        for (int s = 0; s < 4; s++) {
          mbar_wait(emptyb + s * 8, epar);
          expect_load_2d_mc_e(abase + s * A_SLOT + rank * 4096, m32, fullb + s * 8, col + s * 64, row + rank * 32);
        }
        epar ^= 1;
      };
      if (helper) {
#pragma unroll 1
        for (int h = 1; h < 2 * kJobs; h++) refill_shared(&mx32, col0 + (h & 1) * 256, job_row(h >> 1) + w * 64);
      } else {
        const uint32_t xready_peer = map_cta(sb + BAR_XREADY + w * 8, rank ^ 1);
        const unsigned int* oflag = g_flags + ((grp * 4 + kgroup_col(j, 2)) * 2 + w) * 32;
        unsigned int* done_mine = g_flags + kFlagSet + (bid * 2 + w) * 32;
        const unsigned int* done_peer = g_flags + kFlagSet + ((bid ^ 2) * 2 + w) * 32;
        uint32_t nx = 0;
#pragma unroll 1
        for (int rd = 0; rd < kRounds; rd++) {
          const int xrow = (rd * kGroups + grp) * 128 + w * 64;
          if (rd == 0) {
            refill(&mx64, 256, xrow);
          } else {
            poll_flag(done_peer, base + nx);
            store_refill(xrow - kGroups * 128, (j ^ 1) * 256, xrow, rd * kLayers == short_t);
          }
          if (rd * kLayers != short_t) {
#pragma unroll 1
            for (int h = 0; h < 2; h++) refill_shared(&mx32, (kgroup_col(rd == 0 ? 0 : j, 2) + h) * 256, xrow);
          }
#pragma unroll 1
          for (int l = 1; l < kLayers; l++) {
            if (l > 1) poll_flag(done_peer, base + nx);
            store_tile(Flag<false>(), xrow);
            PROF_SVC((rd * kLayers + l - 1) * 2 + w);
            arrive_mapped_e(xready_peer);
            arrive_e(sb + BAR_PUB + w * 8);
            mbar_wait(sb + BAR_XREADY + w * 8, nx & 1);
            fence_async_global();
            refill(&mo64, (j ^ 1) * 256, xrow);
#pragma unroll 1
            for (int h = 0; h < 2; h++) {
              poll_flag(oflag + h * 64, base + nx + 1);
              fence_async_global();
              refill_shared(&mo32, (kgroup_col(j, 2) + h) * 256, xrow);
            }
            if (rank) {
#pragma unroll 1
              for (int s = 0; s < 4; s++) mbar_wait(fullb + s * 8, 1);
            }
            nx++;
            if ((tid & 31) == 0) st_relaxed(done_mine, base + (nx == kRounds * (kLayers - 1) ? kEpoch : nx));
            __syncwarp();
          }
          const int nrow = xrow + kGroups * 128;
          if (rd + 1 == kRounds) {
            poll_flag(done_peer, base + nx);
            store_tile(Flag<true>(), xrow);
          } else {
            refill(&mx64, j * 256, nrow);
          }
          PROF_SVC((rd * kLayers + kLayers - 1) * 2 + w);
        }
      }
    } else {
      const int lane = tid & 31;
      unsigned int* myflag = g_flags + bid * 2 * 32;
      if (lane == 0) { prefetch_map(&mx32); prefetch_map(&mo64); prefetch_map(&mo32); }
      const unsigned int base = *(volatile unsigned int*)myflag;
      auto publish = [&](uint32_t n, uint32_t value) {
#pragma unroll 1
        for (int w = 0; w < 2; w++) {
          mbar_wait(sb + BAR_PUB + w * 8, n & 1);
          asm volatile("fence.acq_rel.gpu;" ::: "memory");
          if (lane == 0) st_relaxed(myflag + w * 32, base + value);
          __syncwarp();
        }
      };
      if (helper) {
        cluster_wait();
#pragma unroll 1
        for (int n = 0; n < kJobs; n++) {
          if (n + 2 < kJobs) {
            const int row = job_row(n + 2);
#pragma unroll 1
            for (int i = 0; i < 8; i++) prefetch_2d_e(&mx64, col0 + rank * 256 + (i & 3) * 64, row + (i >> 2) * 64);
          }
          publish(n, n + 1);
        }
      } else {
        {
          float c[8];
#pragma unroll
          for (int i = 0; i < 8; i++) c[i] = 0.f;
#pragma unroll 1
          for (int l = 0; l < kLayers; l++) {
            const uint4 v = *reinterpret_cast<const uint4*>(bias + l * kDim + j * 256 + lane * 8);
            const uint32_t u[4] = {v.x, v.y, v.z, v.w};
#pragma unroll
            for (int i = 0; i < 4; i++) {
              c[2 * i] += __uint_as_float(u[i] << 16);
              c[2 * i + 1] += __uint_as_float(u[i] & 0xffff0000u);
              uint32_t pk;
              asm("cvt.rn.bf16x2.f32 %0, %1, %2;" : "=r"(pk) : "f"(c[2 * i + 1]), "f"(c[2 * i]));
              asm volatile("st.shared.u32 [%0], %1;" ::"r"(sb + OFF_BIAS + l * 512 + (lane >> 2) * 64 + i * 16 + (lane & 3) * 4),
                           "r"(pk) : "memory");
            }
          }
#pragma unroll
          for (int i = 0; i < 15; i++) {
            const uint32_t one = (lane >> 3) == (lane & 3) ? 0x3f80u << ((lane & 4) * 4) : 0u;
            asm volatile("st.shared.u32 [%0], %1;" ::"r"(sb + OFF_UNIT + i * 128 + lane * 4), "r"(i == 7 ? one : 0u) : "memory");
          }
          fence_async_smem();
          mbar_arrive(sb + BAR_BIAS);
        }
        const __nv_bfloat16* wslice = wptr + bid * 8192;
        prefetch_1d_e(wslice + kDim * kDim, 16384);
        cluster_wait();
        uint32_t nx = 0;
#pragma unroll 1
        for (int rd = 0; rd < kRounds; rd++) {
#pragma unroll 1
          for (int l = 1; l < kLayers; l++) {
            publish(nx, nx + 1 == kRounds * (kLayers - 1) ? kEpoch : nx + 1);
            nx++;
            if (l < kLayers - 1) {
              if (rd == 0) prefetch_1d_e(wslice + (l + 1) * kDim * kDim, 16384);
            } else if (rd + 1 < kRounds) {
              const int nrow = ((rd + 1) * kGroups + grp) * 128;
#pragma unroll 1
              for (int i = 0; i < 8; i++) {
                prefetch_2d_e(&mx64, j * 256 + (i >> 1) * 64, nrow + (i & 1) * 64);
                __nanosleep(300);
              }
              if ((rd + 1) * kLayers == short_t) {
                poll_flag(g_flags + ((4 * kGroups + j) * 2 + 1) * 32, base + job_of_group(grp) + 1);
                fence_async_global();
                constexpr uint32_t order = 0x76325140;
#pragma unroll 1
                for (int i = NP; i < 8; i++)
                  prefetch_2d_e(&mp, j * 256 + ((order >> (i * 4)) & 3) * 64, nrow + ((order >> (i * 4)) & 4) * 16);
#pragma unroll 1
                for (int i = 0; i < 8; i++) {
                  if (i >= NP) mbar_wait(sb + BAR_PFREE + (i - NP) * 8, 0);
                  PROF(776 + i);
                  expect_load_2d_e<true>(sb + OFF_P + (i % NP) * A_SLOT, &mp, sb + BAR_PFULL + i * 8,
                                         j * 256 + ((order >> (i * 4)) & 3) * 64, nrow + ((order >> (i * 4)) & 4) * 16);
                }
              }
            }
          }
        }
      }
    }
    if (warp == (helper ? 3 : 2) && (tid & 31) == 0) PROF_ENDS(1002);
    if (warp == 2) PROF_DUMP();
  } else {
    asm volatile("setmaxnreg.inc.sync.aligned.u32 232;");
    const int lane = tid & 31;
    const int wtid = tid & 127;
    const uint32_t abase = sb + OFF_A + wg * NA * A_SLOT;
    const uint32_t afull = sb + BAR_AFULL + wg * NA * 8;
    const uint32_t rel = map_cta(sb + (wtid == 64 ? BAR_BEMPTY : BAR_AEMPTY + wg * NA * 8), wtid == 32 ? (rank ^ 1) : rank);
    const bool rel_b = wtid == 64;
    const bool rel_ab = (wtid & 31) == 0 && wtid < 96;
    const uint32_t frag0 = __shfl_sync(0xffffffffu, abase + ((wtid >> 5) * 16 + ((lane >> 3) & 1) * 8 + (lane & 7)) * 128 +
                                                        (((lane >> 4) ^ (lane & 7)) << 4), lane);
    const uint64_t adesc0 = desc(((abase & 0x3FFFF) >> 4) | DESC_A_LBO);
    const uint64_t bdesc0 = desc((((sb + OFF_B) & 0x3FFFF) >> 4) | DESC_B_LBO);

    const uint64_t zero = gridDim.y - 1;
    uint64_t adesc_q = adesc0 + zero, bdesc_q = bdesc0 + zero;

    float acc[128];
    uint32_t xr[64];
#pragma unroll
    for (int i = 0; i < 128; i++) acc[i] = kOffset;
#pragma unroll
    for (int i = 0; i < 64; i++) xr[i] = 0;
    int l = 0;
    bool hold = false;
    bool swap = false;
    bool brief = helper;
    int capture_q = helper ? -1 : j;

    auto release = [&](int i, bool with_a) {
      mbar_arrive_mapped_if(rel + bempty_off(i), (i & 1) ? with_a : rel_b);
    };
    auto chunk_staged = [&](int c) {
      __syncwarp();
      arrive_e(sb + BAR_STAGED + (wg * NA + c) * 8);
    };
    auto capture_slot = [&](int p) {
#pragma unroll
      for (int g = 0; g < 4; g++) ldsm4(&xr[(p * 4 + g) * 4], (frag0 ^ (g * 32)) + p * A_SLOT);
    };
    auto swap_half = [&](int p, int half) {
#pragma unroll
      for (int g = half * 2; g < half * 2 + 2; g++) {
        const uint32_t addr = (frag0 ^ (g * 32)) + p * A_SLOT;
        uint32_t n[4];
        ldsm4(n, addr);
        stsm4(addr, &xr[(p * 4 + g) * 4]);
#pragma unroll
        for (int i = 0; i < 4; i++) xr[(p * 4 + g) * 4 + i] = n[i];
      }
      if (half) chunk_staged(p);
    };
    auto chunk_of = [&](int c) { return wg ? (0x7631 >> (c * 4)) & 7 : (0x5420 >> (c * 4)) & 7; };
    auto add_partial = [&](int c) __attribute__((always_inline)) {
      const int n = chunk_of(c);
      const int slot = wg ? (0x1001 >> (c * 4)) & 3 : (0x2120 >> (c * 4)) & 3;
      PROF(768 + wg * 16 + c * 2);
      mbar_spin(sb + BAR_PFULL + n * 8, 0);
      PROF(768 + wg * 16 + c * 2 + 1);
      wg_fence();
      wgmma_n256(acc, ((uint64_t)(128 >> 4) << 32) | ((128 >> 4) << 16) | (((sb + OFF_UNIT + (6 - 2 * c) * 128) & 0x3FFFF) >> 4),
                 ((uint64_t)(256 >> 4) << 32) | ((128 >> 4) << 16) | (((sb + OFF_P + slot * A_SLOT) & 0x3FFFF) >> 4));
    };
    auto issue = [&](int i, uint32_t par, int t, bool wait_b) __attribute__((always_inline)) {
      if (!(i & 1)) mbar_spin(afull + (i >> 1) * 8, par);
      if (wait_b) mbar_spin(sb + BAR_BFULL + i * 8, i == 0 ? (par ^ t ^ 1) & 1 : par);
      const uint64_t adesc = adesc_q + ((i >> 1) * (A_SLOT >> 4) + (i & 1) * 4);
      const uint64_t bdesc = bdesc_q + i * (B_SLOT >> 4);
      wg_fence();
      wgmma_n256(acc, adesc, bdesc);
      wgmma_n256(acc, adesc + 2, bdesc + 128);
      wg_commit();
      if (i == NB - 1) { adesc_q += zero; bdesc_q += zero; }
    };
    auto retire = [&](int i, bool with_a) {
      wg_wait<2>();
      release((i + 6) & 7, with_a);
    };
    auto k_loop = [&](auto first, int t) __attribute__((always_inline)) {
      constexpr bool FIRST = decltype(first)::value;
      const bool inject = FIRST && brief && !helper;
      const uint32_t up = moves_up(t) ? B_SLOT >> 4 : 0;
      auto extras = [&](int q, int i, bool swap_now) __attribute__((always_inline)) {
        if (!FIRST) return;
        if (swap_now) swap_half(((i + 5) >> 1) & 3, (i + 1) & 1);
        if ((i & 1) && q == capture_q) capture_slot(i >> 1);
      };
      auto free_partial = [&](int c) {
        if (FIRST) mbar_arrive_if(sb + BAR_PFREE + chunk_of(c) * 8, inject && rel_b);
      };
#pragma unroll
      for (int i = 1; i < 8; i++) {
        if (!(i & 1)) PROF(t * 32 + wg * 16 + 8 + (i >> 1));
        if ((i == 1 || i == 7) && inject) add_partial(i >> 2);
        issue(i, 0, t, true);
        if (i >= 2) retire(i, rel_ab);
        if (i == 3) free_partial(0);
        extras(0, i, i >= 3 && swap);
      }
      PROF(t * 32 + wg * 16 + 1);
      if (!FIRST || !brief) {
#pragma unroll 1
        for (int q = 1; q < 3; q++) {
#pragma unroll
          for (int i = 0; i < 8; i++) {
            issue(i, q & 1, t, true);
            if (i == 0) PROF(t * 32 + wg * 16 + 3 + q);
            retire(i, rel_ab);
            extras(q, i, i < 3 && swap);
          }
          if (FIRST) swap = false;
          if (q == 1) bdesc_q += up;
        }
      }
      const bool rel_last = rel_b | (hold & rel_ab);
      auto with_a = [&](int slot) { return slot == 7 ? rel_ab : rel_last; };
      constexpr int JOIN = DRAIN + 2;
      constexpr int INJ = JOIN < 3 ? 3 : JOIN;
#pragma unroll
      for (int i = 0; i < DRAIN; i++) {
        issue(i, 1, t, true);
        retire(i, with_a((i + 6) & 7));
        if (i == 1) free_partial(1);
        extras(3, i, i < 3 && swap);
      }
      if (wg == 1) {
        mbar_spin(sb + BAR_BFULL + DRAIN * 8, 1);
        wg_wait<1>();
        release((DRAIN + 6) & 7, with_a((DRAIN + 6) & 7));
        wg_wait<0>();
        release((DRAIN + 7) & 7, with_a((DRAIN + 7) & 7));
        if (DRAIN < 2) free_partial(1);
        PROF(t * 32 + wg * 16 + 12);
#pragma unroll
        for (int i = DRAIN; i < 3; i++) extras(-2, i, swap);
        mbar_spin(sb + BAR_ORDER, t & 1);
        PROF(t * 32 + wg * 16 + 6);
#pragma unroll
        for (int i = DRAIN; i < JOIN; i++) {
          issue(i, 1, t, i != DRAIN);
          extras(3, i, false);
        }
      } else {
        PROF(t * 32 + wg * 16 + 6);
#pragma unroll
        for (int i = DRAIN; i < JOIN; i++) {
          issue(i, 1, t, true);
          retire(i, with_a((i + 6) & 7));
          if (i == 1) free_partial(1);
          extras(3, i, i < 3 && swap);
        }
      }
#pragma unroll
      for (int i = JOIN; i < 8; i++) {
        if ((i == INJ || i == 7) && inject) add_partial(i == INJ ? 2 : 3);
        issue(i, 1, t, true);
        if (i == DCN_ORD) mbar_arrive_if(sb + BAR_ORDER, rel_b & (wg == 0));
        retire(i, rel_last);
        if (i == INJ + 2) free_partial(2);
        extras(3, i, false);
      }
      bdesc_q -= up;
    };

    cluster_wait();
    const int ntiles = helper ? kJobs : kTiles;
    mbar_spin(sb + BAR_BFULL0, 0);
    issue(0, 0, 0, false);
#pragma unroll 1
    for (int t = 0;; t++) {
      hold = (helper || l == kLayers - 1) && (t + 1 < ntiles);
      PROF(t * 32 + wg * 16 + 0);
      if (l == 0) k_loop(Flag<true>(), t);
      else k_loop(Flag<false>(), t);
      if (t == 0 && !helper) mbar_spin(sb + BAR_BIAS, 0);
      const uint32_t bl = sb + OFF_BIAS + l * 512 + ((frag0 >> 3) & 0x30);
      uint32_t bq[8][4];
      auto load_bias = [&](int U) {
        asm volatile("ld.shared.v4.u32 {%0, %1, %2, %3}, [%4];"
                     : "=r"(bq[U][0]), "=r"(bq[U][1]), "=r"(bq[U][2]), "=r"(bq[U][3]) : "r"(bl + U * 64));
      };
#pragma unroll
      for (int U = 0; U < BPRE; U++) load_bias(U);
      uint32_t fa[4];
#pragma unroll
      for (int g = 0; g < 4; g++) asm volatile("xor.b32 %0, %1, %2;" : "=r"(fa[g]) : "r"(frag0), "r"(g * 32));
      wg_wait<1>();
      release(6, false);
      if (t + 1 < ntiles) mbar_spin(sb + BAR_BFULL0, (t + 1) & 1);
      wg_wait<0>();
#pragma unroll
      for (int i = 0; i < 128; i++) asm volatile("" : "+f"(acc[i]) :: "memory");
      release(7, rel_b | (hold & rel_ab));
      PROF(t * 32 + wg * 16 + 2);

      auto pack = [&](int i, float off) {
        uint32_t v;
        asm("cvt.rn.bf16x2.f32 %0, %1, %2;" : "=r"(v) : "f"(acc[i * 2 + 1] - off), "f"(acc[i * 2] - off));
        return v;
      };
      auto cross = [&](int T, int i, float off) {
        uint32_t s2 = pack(T * 4 + i, off), o;
        asm("add.rn.bf16x2 %0, %1, %2;" : "=r"(s2) : "r"(s2), "r"(bq[T >> 1][(T & 1) * 2 + (i >> 1)]));
        asm("fma.rn.bf16x2 %0, %1, %2, %1;" : "=r"(o) : "r"(xr[T * 4 + i]), "r"(s2));
        return o;
      };
      auto reset = [&](int T) {
#pragma unroll
        for (int i = T * 8; i < T * 8 + 8; i += 4)
          asm volatile("ld.volatile.shared.v4.f32 {%0, %1, %2, %3}, [%4];"
                       : "+f"(acc[i]), "+f"(acc[i + 1]), "+f"(acc[i + 2]), "+f"(acc[i + 3]) : "r"(sb + OFF_INIT));
      };
      auto offset_for = [&](int T) { return T >= LAG ? acc[(T - LAG) * 8 + 7] : kOffset; };
      if (helper) {
        uint32_t id;
        asm volatile("mov.u32 %0, %%tid.x;" : "=r"(id));
        __nv_bfloat16* dst = optr + (size_t)(job_row(t) + wg * 64) * kDim + j * 256 + (id & 127) * 2;
        uint64_t pol;
        asm volatile("createpolicy.fractional.L2::evict_first.b64 %0, 1.0;" : "=l"(pol));
#pragma unroll
        for (int T = 0; T < 16; T++) {
#pragma unroll
          for (int i = 0; i < 4; i++)
            asm volatile("st.global.L2::cache_hint.b32 [%0], %1, %2;"
                         ::"l"(dst + (T * 4 + (i ^ 1)) * kDim), "r"(pack(T * 4 + i, offset_for(T))), "l"(pol) : "memory");
          reset(T);
        }
        asm volatile("bar.sync %0, 128;" ::"r"(wg + 1) : "memory");
        mbar_arrive_if(sb + BAR_PUB + wg * 8, rel_b);
      } else if (hold) {
#pragma unroll
        for (int T = 0; T < 16; T++) {
#pragma unroll
          for (int i = 0; i < 4; i++) xr[T * 4 + i] = cross(T, i, offset_for(T));
          if ((T & 1) && (T >> 1) + BPRE < 8) load_bias((T >> 1) + BPRE);
          reset(T);
        }
      } else {
        uint32_t o[16][4];
#pragma unroll
        for (int T = 0; T < 16; T++) {
          float off = kOffset;
          if (DCN_ELAG && T >= DCN_ELAG)
            asm("lop3.b32 %0, %1, %2, %3, 0xea;" : "=f"(off) : "r"(o[T - DCN_ELAG][3]), "r"((uint32_t)zero), "f"(kOffset));
#pragma unroll
          for (int i = 0; i < 4; i++) o[T][i] = cross(T, i, off);
          stsm4(fa[T & 3] + (T >> 2) * A_SLOT, o[T]);
          if ((T & 3) == 3) chunk_staged(T >> 2);
          if ((T & 1) && (T >> 1) + BPRE < 8) load_bias((T >> 1) + BPRE);
        }
        PROF(t * 32 + wg * 16 + 7);
      }
      PROF(t * 32 + wg * 16 + 3);
      if (t + 1 == ntiles) break;
      issue(0, 0, 0, false);
      if (helper || ++l == kLayers) l = 0;
      swap = hold && !helper;
      brief = helper || t + 1 == short_t;
      capture_q = -1;
    }
  }
}

__global__ void __launch_bounds__(256) dcn_fallback(const __nv_bfloat16* __restrict__ x0, const __nv_bfloat16* __restrict__ w,
                                                    const __nv_bfloat16* __restrict__ b, __nv_bfloat16* __restrict__ out) {
  __shared__ float xs[8][kDim];
  const size_t r0 = (size_t)blockIdx.x * 8;
  for (int i = threadIdx.x; i < 8 * kDim; i += 256) xs[i / kDim][i % kDim] = __bfloat162float(x0[r0 * kDim + i]);
  __syncthreads();
  for (int l = 0; l < kLayers; l++) {
    float a[4][8] = {};
    for (int k = 0; k < kDim; k++) {
#pragma unroll
      for (int c = 0; c < 4; c++) {
        const float wv = __bfloat162float(w[((size_t)l * kDim + k) * kDim + c * 256 + threadIdx.x]);
#pragma unroll
        for (int r = 0; r < 8; r++) a[c][r] += xs[r][k] * wv;
      }
    }
    __syncthreads();
#pragma unroll
    for (int c = 0; c < 4; c++) {
      const int n = c * 256 + threadIdx.x;
#pragma unroll
      for (int r = 0; r < 8; r++) {
        const float v = __bfloat162float(x0[(r0 + r) * kDim + n]) * (a[c][r] + __bfloat162float(b[l * kDim + n])) + xs[r][n];
        xs[r][n] = __bfloat162float(__float2bfloat16(v));
      }
    }
    __syncthreads();
  }
  for (int i = threadIdx.x; i < 8 * kDim; i += 256) out[r0 * kDim + i] = __float2bfloat16(xs[i / kDim][i % kDim]);
}

typedef CUresult (*EncodeFn)(CUtensorMap*, CUtensorMapDataType, cuuint32_t, void*, const cuuint64_t*, const cuuint64_t*,
                             const cuuint32_t*, const cuuint32_t*, CUtensorMapInterleave, CUtensorMapSwizzle,
                             CUtensorMapL2promotion, CUtensorMapFloatOOBfill);

static void make_map_2d(EncodeFn enc, CUtensorMap* m, void* ptr, uint64_t rows, uint32_t box_rows,
                        CUtensorMapSwizzle swizzle = CU_TENSOR_MAP_SWIZZLE_128B) {
  cuuint64_t dims[2] = {(cuuint64_t)kDim, rows};
  cuuint64_t strides[1] = {kDim * 2};
  cuuint32_t box[2] = {64, box_rows};
  cuuint32_t es[2] = {1, 1};
  enc(m, CU_TENSOR_MAP_DATA_TYPE_BFLOAT16, 2, ptr, dims, strides, box, es, CU_TENSOR_MAP_INTERLEAVE_NONE,
      swizzle, CU_TENSOR_MAP_L2_PROMOTION_L2_128B, CU_TENSOR_MAP_FLOAT_OOB_FILL_NONE);
}

}

extern "C" void kernel_launch(void* const* d_in, const int* in_sizes, int n_in, void* d_out, int out_size) {
  using namespace dcn;
  (void)in_sizes; (void)n_in; (void)out_size;
  void* fn = nullptr;
  cudaDriverEntryPointQueryResult qr;
  cudaGetDriverEntryPoint("cuTensorMapEncodeTiled", &fn, cudaEnableDefault, &qr);
  EncodeFn enc = (EncodeFn)fn;
  CUtensorMap mx64, mx32, mo64, mo32, mw, mp;
  make_map_2d(enc, &mx64, d_in[0], kRows, 64);
  make_map_2d(enc, &mx32, d_in[0], kRows, 32);
  make_map_2d(enc, &mo64, d_out, kRows, 64);
  make_map_2d(enc, &mo32, d_out, kRows, 32);
  make_map_2d(enc, &mp, d_out, kRows, 64, CU_TENSOR_MAP_SWIZZLE_NONE);
  {
    cuuint64_t dims[3] = {64, (cuuint64_t)kLayers * kDim, kDim / 64};
    cuuint64_t strides[2] = {kDim * 2, 128};
    cuuint32_t box[3] = {64, 32, 4};
    cuuint32_t es[3] = {1, 1, 1};
    enc(&mw, CU_TENSOR_MAP_DATA_TYPE_BFLOAT16, 3, d_in[1], dims, strides, box, es, CU_TENSOR_MAP_INTERLEAVE_NONE,
        CU_TENSOR_MAP_SWIZZLE_128B, CU_TENSOR_MAP_L2_PROMOTION_L2_128B, CU_TENSOR_MAP_FLOAT_OOB_FILL_NONE);
  }
  const __nv_bfloat16* x0 = (const __nv_bfloat16*)d_in[0];
  const __nv_bfloat16* w = (const __nv_bfloat16*)d_in[1];
  const __nv_bfloat16* b = (const __nv_bfloat16*)d_in[2];
  __nv_bfloat16* out = (__nv_bfloat16*)d_out;
  constexpr int smem = SMEM_BYTES + PROF_SMEM;
  cudaFuncSetAttribute(dcn_kernel, cudaFuncAttributeMaxDynamicSharedMemorySize, smem);

  cudaLaunchConfig_t cfg = {};
  cfg.gridDim = dim3(4 * kGroups + 4);
  cfg.blockDim = dim3(384);
  cfg.dynamicSmemBytes = smem;
  cudaLaunchAttribute attr;
  attr.id = cudaLaunchAttributeClusterDimension;
  attr.val.clusterDim.x = 2;
  attr.val.clusterDim.y = 1;
  attr.val.clusterDim.z = 1;
  cfg.attrs = &attr;
  cfg.numAttrs = 1;
  int clusters = 0;
  cudaOccupancyMaxActiveClusters(&clusters, dcn_kernel, &cfg);
  if (clusters >= 2 * kGroups) {
    const int grid = 4 * kGroups + (clusters >= 2 * kGroups + 2 ? 4 : 0);
    dcn_kernel<<<grid, 384, smem>>>(mx64, mx32, mo64, mo32, mw, mp, x0, w, b, out);
  } else {
    dcn_fallback<<<kRows / 8, 256>>>(x0, w, b, out);
  }
}
```

```cpp
#include <cuda_runtime.h>
#include <cuda.h>
#include <cuda_bf16.h>
#include <stdint.h>

namespace dcn {

__device__ __forceinline__ void wgmma_n256(float (&d)[128], uint64_t da, uint64_t db) {
  asm volatile("wgmma.mma_async.sync.aligned.m64n256k16.f32.bf16.bf16 "
    "{%0, %1, %2, %3, %4, %5, %6, %7, %8, %9, %10, %11, %12, %13, %14, %15, %16, %17, %18, %19, %20, %21, %22, %23, %24, %25, %26, %27, %28, %29, %30, %31, %32, %33, %34, %35, %36, %37, %38, %39, %40, %41, %42, %43, %44, %45, %46, %47, %48, %49, %50, %51, %52, %53, %54, %55, %56, %57, %58, %59, %60, %61, %62, %63, %64, %65, %66, %67, %68, %69, %70, %71, %72, %73, %74, %75, %76, %77, %78, %79, %80, %81, %82, %83, %84, %85, %86, %87, %88, %89, %90, %91, %92, %93, %94, %95, %96, %97, %98, %99, %100, %101, %102, %103, %104, %105, %106, %107, %108, %109, %110, %111, %112, %113, %114, %115, %116, %117, %118, %119, %120, %121, %122, %123, %124, %125, %126, %127}, "
    "%128, %129, 1, 1, 1, 0, 1;\n"
    : "+f"(d[0]), "+f"(d[1]), "+f"(d[2]), "+f"(d[3]), "+f"(d[4]), "+f"(d[5]), "+f"(d[6]), "+f"(d[7]), "+f"(d[8]), "+f"(d[9]), "+f"(d[10]), "+f"(d[11]), "+f"(d[12]), "+f"(d[13]), "+f"(d[14]), "+f"(d[15]), "+f"(d[16]), "+f"(d[17]), "+f"(d[18]), "+f"(d[19]), "+f"(d[20]), "+f"(d[21]), "+f"(d[22]), "+f"(d[23]), "+f"(d[24]), "+f"(d[25]), "+f"(d[26]), "+f"(d[27]), "+f"(d[28]), "+f"(d[29]), "+f"(d[30]), "+f"(d[31]), "+f"(d[32]), "+f"(d[33]), "+f"(d[34]), "+f"(d[35]), "+f"(d[36]), "+f"(d[37]), "+f"(d[38]), "+f"(d[39]), "+f"(d[40]), "+f"(d[41]), "+f"(d[42]), "+f"(d[43]), "+f"(d[44]), "+f"(d[45]), "+f"(d[46]), "+f"(d[47]), "+f"(d[48]), "+f"(d[49]), "+f"(d[50]), "+f"(d[51]), "+f"(d[52]), "+f"(d[53]), "+f"(d[54]), "+f"(d[55]), "+f"(d[56]), "+f"(d[57]), "+f"(d[58]), "+f"(d[59]), "+f"(d[60]), "+f"(d[61]), "+f"(d[62]), "+f"(d[63]), "+f"(d[64]), "+f"(d[65]), "+f"(d[66]), "+f"(d[67]), "+f"(d[68]), "+f"(d[69]), "+f"(d[70]), "+f"(d[71]), "+f"(d[72]), "+f"(d[73]), "+f"(d[74]), "+f"(d[75]), "+f"(d[76]), "+f"(d[77]), "+f"(d[78]), "+f"(d[79]), "+f"(d[80]), "+f"(d[81]), "+f"(d[82]), "+f"(d[83]), "+f"(d[84]), "+f"(d[85]), "+f"(d[86]), "+f"(d[87]), "+f"(d[88]), "+f"(d[89]), "+f"(d[90]), "+f"(d[91]), "+f"(d[92]), "+f"(d[93]), "+f"(d[94]), "+f"(d[95]), "+f"(d[96]), "+f"(d[97]), "+f"(d[98]), "+f"(d[99]), "+f"(d[100]), "+f"(d[101]), "+f"(d[102]), "+f"(d[103]), "+f"(d[104]), "+f"(d[105]), "+f"(d[106]), "+f"(d[107]), "+f"(d[108]), "+f"(d[109]), "+f"(d[110]), "+f"(d[111]), "+f"(d[112]), "+f"(d[113]), "+f"(d[114]), "+f"(d[115]), "+f"(d[116]), "+f"(d[117]), "+f"(d[118]), "+f"(d[119]), "+f"(d[120]), "+f"(d[121]), "+f"(d[122]), "+f"(d[123]), "+f"(d[124]), "+f"(d[125]), "+f"(d[126]), "+f"(d[127])
    : "l"(da), "l"(db));
}

constexpr int kDim = 1024;
constexpr int kRows = 16384;
constexpr int kLayers = 6;
constexpr int kGroups = 32;
constexpr int kRounds = kRows / 128 / kGroups;
constexpr int kTiles = kRounds * kLayers;

constexpr int kJobs = kGroups;
constexpr int kEpoch = 32;
constexpr int NA = 4;
constexpr int NB = 8;
#define DCN_OFF 85.333336f
constexpr float kOffset = DCN_OFF;
constexpr float kTrunc = 64 * 0.375f / 131072;
#define DCN_DRAIN 1
#define DCN_LAG 3
constexpr int DRAIN = DCN_DRAIN;
constexpr int LAG = DCN_LAG;
#define DCN_AS 0
#define DCN_ORD 7
#define DCN_BPRE 6
#define DCN_ELAG 0
constexpr int BPRE = DCN_BPRE;
constexpr int A_SLOT = 8192;
constexpr int B_SLOT = 16384;
constexpr int OFF_B = 0;
constexpr int NP = 3;
constexpr int OFF_P = OFF_B + NB * B_SLOT;
constexpr int OFF_A = OFF_P + NP * A_SLOT;
constexpr int OFF_UNIT = OFF_A + 2 * NA * A_SLOT;
constexpr int OFF_BIAS = OFF_UNIT + 2048;
constexpr int OFF_INIT = OFF_BIAS + kLayers * 256 * 2;
constexpr int OFF_BAR = OFF_INIT + 16;
constexpr int BAR_BFULL = OFF_BAR;
constexpr int BAR_BFULL0 = BAR_BFULL + NB * 8;
constexpr int BAR_BEMPTY = BAR_BFULL0 + 8;
constexpr int BAR_AFULL = BAR_BEMPTY + NB * 8;
constexpr int BAR_AEMPTY = BAR_AFULL + 2 * NA * 8;
constexpr int BAR_XREADY = BAR_AEMPTY + 2 * NA * 8;
constexpr int BAR_PUB = BAR_XREADY + 16;
constexpr int BAR_PFULL = BAR_PUB + 16;
constexpr int BAR_PFREE = BAR_PFULL + 8 * 8;
constexpr int BAR_STAGED = BAR_PFREE + 8 * 8;
constexpr int BAR_ORDER = BAR_STAGED + 2 * NA * 8;
constexpr int BAR_BIAS = BAR_ORDER + 8;
constexpr int SMEM_BYTES = BAR_BIAS + 8;
static_assert(SMEM_BYTES <= 232448, "shared memory budget");

constexpr int kFlagSet = 4 * (kGroups + 1) * 2 * 32;
__device__ unsigned int g_flags[2 * kFlagSet];

__device__ __forceinline__ uint32_t smem_u32(const void* p) { return (uint32_t)__cvta_generic_to_shared(p); }
__device__ __forceinline__ void mbar_init(uint32_t bar, int cnt) {
  asm volatile("mbarrier.init.shared::cta.b64 [%0], %1;" ::"r"(bar), "r"(cnt) : "memory");
}
__device__ __forceinline__ void mbar_arrive(uint32_t bar) {
  asm volatile("mbarrier.arrive.shared::cta.b64 _, [%0];" ::"r"(bar) : "memory");
}
__device__ __forceinline__ uint32_t map_cta(uint32_t addr, uint32_t cta) {
  uint32_t r;
  asm volatile("mapa.shared::cluster.u32 %0, %1, %2;" : "=r"(r) : "r"(addr), "r"(cta));
  return r;
}
__device__ __forceinline__ void mbar_arrive_mapped(uint32_t cluster_addr) {
  asm volatile("mbarrier.arrive.shared::cluster.b64 _, [%0];" ::"r"(cluster_addr) : "memory");
}
__device__ __forceinline__ void mbar_arrive_mapped_if(uint32_t cluster_addr, bool pred) {
  asm volatile("{\n.reg .pred p;\nsetp.ne.u32 p, %1, 0;\n@p mbarrier.arrive.shared::cluster.b64 _, [%0];\n}"
               ::"r"(cluster_addr), "r"((uint32_t)pred) : "memory");
}
__device__ __forceinline__ void mbar_arrive_if(uint32_t bar, bool pred) {
  asm volatile("{\n.reg .pred p;\nsetp.ne.u32 p, %1, 0;\n@p mbarrier.arrive.shared::cta.b64 _, [%0];\n}"
               ::"r"(bar), "r"((uint32_t)pred) : "memory");
}
__device__ __forceinline__ void mbar_wait(uint32_t bar, uint32_t parity) {
  asm volatile(
      "{\n.reg .pred p;\n.reg .u32 c;\n"
      "mbarrier.try_wait.parity.shared::cta.b64 p, [%0], %1;\n"
      "@p bra DONE;\n"
      "mov.u32 c, 0;\n"
      "LOOP:\n"
      "mbarrier.try_wait.parity.shared::cta.b64 p, [%0], %1;\n"
      "@p bra DONE;\n"
      "add.u32 c, c, 1;\n"
      "setp.lt.u32 p, c, 4194304;\n"
      "@p bra LOOP;\n"
      "trap;\n"
      "DONE:\n}"
      ::"r"(bar), "r"(parity) : "memory");
}
__device__ __forceinline__ void mbar_spin(uint32_t bar, uint32_t parity) {
  asm volatile(
      "{\n.reg .pred p;\n"
      "LOOP:\n"
      "mbarrier.try_wait.parity.shared::cta.b64 p, [%0], %1;\n"
      "@!p bra LOOP;\n}"
      ::"r"(bar), "r"(parity) : "memory");
}
#define ELECT_BEGIN "{\n.reg .pred e;\nelect.sync _|e, 0xffffffff;\n"
template <bool STREAM> __device__ __forceinline__ void expect_load_2d_e(uint32_t dst, const CUtensorMap* m, uint32_t bar, int c0, int c1) {
  if (STREAM) {
    asm volatile(ELECT_BEGIN ".reg .b64 pol;\ncreatepolicy.fractional.L2::evict_first.b64 pol, 1.0;\n"
                 "@e mbarrier.arrive.expect_tx.shared::cta.b64 _, [%2], 8192;\n"
                 "@e cp.async.bulk.tensor.2d.shared::cluster.global.mbarrier::complete_tx::bytes.L2::cache_hint [%0], [%1, {%3, %4}], [%2], pol;\n}"
                 ::"r"(dst), "l"(m), "r"(bar), "r"(c0), "r"(c1) : "memory");
  } else {
    asm volatile(ELECT_BEGIN
                 "@e mbarrier.arrive.expect_tx.shared::cta.b64 _, [%2], 8192;\n"
                 "@e cp.async.bulk.tensor.2d.shared::cluster.global.mbarrier::complete_tx::bytes [%0], [%1, {%3, %4}], [%2];\n}"
                 ::"r"(dst), "l"(m), "r"(bar), "r"(c0), "r"(c1) : "memory");
  }
}
__device__ __forceinline__ void expect_load_2d_mc_e(uint32_t dst, const CUtensorMap* m, uint32_t bar, int c0, int c1) {
  asm volatile(ELECT_BEGIN ".reg .b64 pol;\ncreatepolicy.fractional.L2::evict_first.b64 pol, 1.0;\n"
               "@e mbarrier.arrive.expect_tx.shared::cta.b64 _, [%2], 8192;\n"
               "@e cp.async.bulk.tensor.2d.shared::cluster.global.mbarrier::complete_tx::bytes.multicast::cluster.L2::cache_hint [%0], [%1, {%3, %4}], [%2], %5, pol;\n}"
               ::"r"(dst), "l"(m), "r"(bar), "r"(c0), "r"(c1), "h"((uint16_t)3) : "memory");
}
__device__ __forceinline__ void expect_load_3d_e(uint32_t dst, const CUtensorMap* m, uint32_t bar, int c0, int c1, int c2) {
  asm volatile(ELECT_BEGIN
               "@e mbarrier.arrive.expect_tx.shared::cta.b64 _, [%2], 16384;\n"
               "@e cp.async.bulk.tensor.3d.shared::cluster.global.mbarrier::complete_tx::bytes [%0], [%1, {%3, %4, %5}], [%2];\n}"
               ::"r"(dst), "l"(m), "r"(bar), "r"(c0), "r"(c1), "r"(c2) : "memory");
}
template <bool STREAM> __device__ __forceinline__ void store_2d_e(const CUtensorMap* m, uint32_t src, int c0, int c1) {
  if (STREAM) {
    asm volatile(ELECT_BEGIN ".reg .b64 pol;\ncreatepolicy.fractional.L2::evict_first.b64 pol, 1.0;\n"
                 "@e cp.async.bulk.tensor.2d.global.shared::cta.bulk_group.L2::cache_hint [%0, {%2, %3}], [%1], pol;\n}"
                 ::"l"(m), "r"(src), "r"(c0), "r"(c1) : "memory");
  } else {
    asm volatile(ELECT_BEGIN
                 "@e cp.async.bulk.tensor.2d.global.shared::cta.bulk_group [%0, {%2, %3}], [%1];\n}"
                 ::"l"(m), "r"(src), "r"(c0), "r"(c1) : "memory");
  }
}
__device__ __forceinline__ void prefetch_2d_e(const CUtensorMap* m, int c0, int c1) {
  asm volatile(ELECT_BEGIN
               "@e cp.async.bulk.prefetch.tensor.2d.L2.global [%0, {%1, %2}];\n}"
               ::"l"(m), "r"(c0), "r"(c1) : "memory");
}
__device__ __forceinline__ void prefetch_1d_e(const void* ptr, uint32_t bytes) {
  asm volatile(ELECT_BEGIN
               "@e cp.async.bulk.prefetch.L2.global [%0], %1;\n}"
               ::"l"(ptr), "r"(bytes) : "memory");
}
__device__ __forceinline__ void paced_load_3d_e(uint32_t dst, const CUtensorMap* m, uint32_t bar, int c0, int c1, int c2) {
  asm volatile(ELECT_BEGIN
               "@e mbarrier.arrive.expect_tx.shared::cta.b64 _, [%2], 16384;\n"
               "nanosleep.u32 128;\n"
               "@e cp.async.bulk.tensor.3d.shared::cluster.global.mbarrier::complete_tx::bytes [%0], [%1, {%3, %4, %5}], [%2];\n}"
               ::"r"(dst), "l"(m), "r"(bar), "r"(c0), "r"(c1), "r"(c2) : "memory");
}
__device__ __forceinline__ void arrive_mapped_e(uint32_t cluster_addr) {
  asm volatile(ELECT_BEGIN "@e mbarrier.arrive.shared::cluster.b64 _, [%0];\n}" ::"r"(cluster_addr) : "memory");
}
__device__ __forceinline__ void arrive_e(uint32_t bar) {
  asm volatile(ELECT_BEGIN "@e mbarrier.arrive.shared::cta.b64 _, [%0];\n}" ::"r"(bar) : "memory");
}
__device__ __forceinline__ void bulk_commit() { asm volatile("cp.async.bulk.commit_group;" ::: "memory"); }
template <int N> __device__ __forceinline__ void bulk_wait() { asm volatile("cp.async.bulk.wait_group %0;" ::"n"(N) : "memory"); }
__device__ __forceinline__ void wg_fence() { asm volatile("wgmma.fence.sync.aligned;" ::: "memory"); }
__device__ __forceinline__ void wg_commit() { asm volatile("wgmma.commit_group.sync.aligned;" ::: "memory"); }
template <int N> __device__ __forceinline__ void wg_wait() { asm volatile("wgmma.wait_group.sync.aligned %0;" ::"n"(N) : "memory"); }
__device__ __forceinline__ void fence_async_global() { asm volatile("fence.proxy.async.global;" ::: "memory"); }
__device__ __forceinline__ void st_relaxed(unsigned int* p, unsigned int v) {
  asm volatile("st.relaxed.gpu.global.u32 [%0], %1;" ::"l"(p), "r"(v) : "memory");
}
__device__ __forceinline__ unsigned int ld_acquire(const unsigned int* p) {
  unsigned int v;
  asm volatile("ld.acquire.gpu.global.u32 %0, [%1];" : "=r"(v) : "l"(p) : "memory");
  return v;
}
__device__ __forceinline__ void ldsm4(uint32_t* r, uint32_t addr) {
  asm volatile("ldmatrix.sync.aligned.m8n8.x4.shared.b16 {%0, %1, %2, %3}, [%4];"
               : "=r"(r[0]), "=r"(r[1]), "=r"(r[2]), "=r"(r[3]) : "r"(addr) : "memory");
}
__device__ __forceinline__ void stsm4(uint32_t addr, const uint32_t* r) {
  asm volatile("stmatrix.sync.aligned.m8n8.x4.shared.b16 [%0], {%1, %2, %3, %4};"
               ::"r"(addr), "r"(r[0]), "r"(r[1]), "r"(r[2]), "r"(r[3]) : "memory");
}
template <bool V> struct Flag { static constexpr bool value = V; };
__device__ __forceinline__ void fence_async_smem() { asm volatile("fence.proxy.async.shared::cta;" ::: "memory"); }
__device__ __forceinline__ void cluster_arrive_relaxed() { asm volatile("barrier.cluster.arrive.relaxed.aligned;" ::: "memory"); }
__device__ __forceinline__ void cluster_wait() { asm volatile("barrier.cluster.wait.acquire.aligned;" ::: "memory"); }
__device__ __forceinline__ void prefetch_map(const CUtensorMap* m) {
  asm volatile("prefetch.tensormap [%0];" ::"l"(m) : "memory");
}
__device__ __forceinline__ void poll_flag(const unsigned int* ptr, unsigned int target) {
  asm volatile(
      "{\n.reg .pred p;\n.reg .u32 c;\n.reg .s32 v;\n"
      "mov.u32 c, 0;\n"
      "LOOP:\n"
      "ld.acquire.gpu.global.s32 v, [%0];\n"
      "sub.s32 v, v, %1;\n"
      "setp.ge.s32 p, v, 0;\n"
      "@p bra DONE;\n"
      "add.u32 c, c, 1;\n"
      "setp.lt.u32 p, c, 4194304;\n"
      "@p bra LOOP;\n"
      "trap;\n"
      "DONE:\n}"
      ::"l"(ptr), "r"(target) : "memory");
}

constexpr uint32_t DESC_HI = (1024u >> 4) | (1u << 30);
__device__ __forceinline__ uint64_t desc(uint32_t lo) { return ((uint64_t)DESC_HI << 32) | lo; }
constexpr uint32_t DESC_A_LBO = 1u << 16;
constexpr uint32_t DESC_B_LBO = (4096u >> 4) << 16;

__host__ __device__ constexpr int bempty_off(int slot) { return ((slot & 1) ? 0 : 32) + (slot >> 1) * 8; }

__device__ __forceinline__ int kgroup_col(int j, int q) {
  return q == 0 ? j : (q == 1 ? (j ^ 1) : (((j ^ 2) & ~1) + (q - 2)));
}

__device__ __forceinline__ int role_of_cluster(int c) {
  const int a = c - 4;
  const int b = c - 36, r = (b * 37) >> 8;
  const int first = (a & ~7) + (a & 3) * 2 + ((a >> 2) & 1);
  const int second = 32 + r * 8 + ((0x7531640 >> (((b - r * 7) * 4) & 31)) & 7);
  return c >= 2 * kGroups ? c : (c >= 36 ? second : (c >= 4 ? first : 34 + c * 8));
}
__device__ __forceinline__ int helped_round(int grp) { return (grp & 2) ? (grp & 3) - 1 : 3; }
__device__ __forceinline__ int job_of_group(int grp) {
  return (grp & 2) ? (grp & 1) * 8 + (grp >> 2) : 16 + (grp >> 2) * 2 + (grp & 1);
}
__device__ __forceinline__ int job_row(int n) {
  const int grp = n < 16 ? (n & 7) * 4 + 2 + (n >> 3) : ((n - 16) >> 1) * 4 + (n & 1);
  return (helped_round(grp) * kGroups + grp) * 128;
}

#define PROF_ENDS(idx) do {} while (0)
#define PROF_SVC(idx) do {} while (0)
#define PROF_SKEW(idx) do {} while (0)
#define PROF(idx) do {} while (0)
#define PROF_DUMP() do {} while (0)
constexpr int PROF_SMEM = 0;

__global__ void __cluster_dims__(2, 1, 1) __launch_bounds__(384, 1)
dcn_kernel(const __grid_constant__ CUtensorMap mx64, const __grid_constant__ CUtensorMap mx32,
           const __grid_constant__ CUtensorMap mo64, const __grid_constant__ CUtensorMap mo32,
           const __grid_constant__ CUtensorMap mw, const __grid_constant__ CUtensorMap mp,
           const __nv_bfloat16* __restrict__ xptr,
           const __nv_bfloat16* __restrict__ wptr, const __nv_bfloat16* __restrict__ bias, __nv_bfloat16* optr) {
  extern __shared__ __align__(1024) uint8_t smem_raw[];
  const uint32_t sb = smem_u32(smem_raw);
  const int tid = threadIdx.x;
  if (tid == 256) {
    prefetch_map(&mw);
    prefetch_map(&mx64);
    mbar_init(sb + BAR_BFULL0, 1);
    mbar_init(sb + BAR_BFULL + 8, 1);
    mbar_init(sb + BAR_AFULL, 1);
    mbar_init(sb + BAR_AFULL + NA * 8, 1);
    asm volatile("fence.mbarrier_init.release.cluster;" ::: "memory");
  }
  const int wg = __shfl_sync(0xffffffffu, tid >> 7, 0);
  const int warp = __shfl_sync(0xffffffffu, (tid >> 5) & 3, 0);
  const int bid = role_of_cluster(blockIdx.x >> 1) * 2 + (blockIdx.x & 1);
  const int j = bid & 3;
  const int grp = bid >> 2;
  const uint32_t rank = j & 1;
  const bool helper = grp == kGroups;
  const int short_t = (gridDim.x > 4 * kGroups && !helper) ? helped_round(grp) * kLayers : -8;
  const unsigned lend = helper ? ~0u : 1u;
  auto moves_up = [&](int t) { return (unsigned)(t + 1 - short_t) > lend; };
  if (tid == 0) PROF_ENDS(1000);

  const int col0 = helper ? kgroup_col(j, 2) * 256 : 0;
  const int row0 = helper ? job_row(0) : grp * 128;
  if (tid < 32 && !helper) {
    asm volatile("prefetch.global.L2 [%0];" ::"l"(wptr + (size_t)((grp & 7) * 8 + (tid >> 2)) * kDim + j * 256 + (tid & 3) * 64));
    asm volatile("prefetch.global.L2 [%0];" ::"l"(xptr + (size_t)(row0 + j * 32 + tid) * kDim));
  }
  auto first_loads = [&](int s) {
    const int col = col0 + s * 64;
    expect_load_3d_e(sb + OFF_B + 2 * s * B_SLOT, &mw, sb + (s ? BAR_BFULL + 2 * s * 8 : BAR_BFULL0), 0, col, j * 4);
    expect_load_2d_e<false>(sb + OFF_A + s * A_SLOT, &mx64, sb + BAR_AFULL + s * 8, col, row0);
    expect_load_3d_e(sb + OFF_B + (2 * s + 1) * B_SLOT, &mw, sb + BAR_BFULL + (2 * s + 1) * 8, 0, col + 32, j * 4);
    expect_load_2d_e<false>(sb + OFF_A + (NA + s) * A_SLOT, &mx64, sb + BAR_AFULL + (NA + s) * 8, col, row0 + 64);
  };
  if (wg == 2 && warp == 0) first_loads(0);
  if (tid == 288) {
    if (sb & 1023) asm volatile("trap;");
#pragma unroll
    for (int i = 0; i < NB; i++) mbar_init(sb + BAR_BEMPTY + i * 8, 2);
#pragma unroll
    for (int i = 0; i < 2 * NA; i++) { mbar_init(sb + BAR_AEMPTY + i * 8, 2); mbar_init(sb + BAR_STAGED + i * 8, 4); }
    asm volatile("fence.mbarrier_init.release.cluster;" ::: "memory");
  }
  if (tid == 352) {
#pragma unroll
    for (int i = 0; i < 8; i++) { mbar_init(sb + BAR_PFULL + i * 8, 1); mbar_init(sb + BAR_PFREE + i * 8, 1); }
    asm volatile("fence.mbarrier_init.release.cluster;" ::: "memory");
  }
  if (tid == 320) {
#pragma unroll
    for (int i = 0; i < NB; i++)
      if (i != 1) mbar_init(sb + BAR_BFULL + i * 8, 1);
#pragma unroll
    for (int i = 0; i < 2 * NA; i++)
      if (i % NA) mbar_init(sb + BAR_AFULL + i * 8, 1);
#pragma unroll
    for (int i = 0; i < 4; i++) mbar_init(sb + BAR_XREADY + i * 8, 1);
    mbar_init(sb + BAR_ORDER, 1);
    mbar_init(sb + BAR_BIAS, 32);
    asm volatile("st.shared.v4.f32 [%0], {%1, %1, %1, %1};" ::"r"(sb + OFF_INIT), "f"(kOffset) : "memory");
    asm volatile("fence.mbarrier_init.release.cluster;" ::: "memory");
  }
  __syncthreads();
  cluster_arrive_relaxed();

  if (wg == 2) {
    asm volatile("setmaxnreg.dec.sync.aligned.u32 40;");
    if (warp == 0) {
#pragma unroll 1
      for (int s = 1; s < 4; s++) first_loads(s);
      cluster_wait();
      uint32_t par = 0;
      int l = 0;
      const int ntiles = helper ? kJobs : kTiles;
#pragma unroll 1
      for (int t = 0; t < ntiles; t++) {
        const int jo = (t == 0 && !helper) ? 0 : j;
        const int q_end = t == short_t ? 2 : 4;
#pragma unroll 1
        for (int q = (helper ? 2 : 0) + (t == 0); q < q_end; q++) {
          const int krow = l * kDim + kgroup_col(jo, q) * 256;
          if (q == (helper ? 2 : 0)) {
            const bool early = moves_up(t - 1);
#pragma unroll
            for (int i = 0; i < NB; i++) {
              if (i > 0 || !early) mbar_spin(sb + BAR_BEMPTY + (early && i > 0 ? bempty_off(i - 1) : bempty_off(i)), par);
              if (i <= DRAIN && early) __nanosleep(128);
              expect_load_3d_e(sb + OFF_B + i * B_SLOT, &mw, sb + (i ? BAR_BFULL + i * 8 : BAR_BFULL0), 0, krow + i * 32, j * 4);
              PROF_SKEW(t * 32 + q * 8 + i);
            }
          } else {
            const bool up = q >= 2 && moves_up(t);
            const bool late = up && q == 2;
            const uint32_t dst = sb + OFF_B + (up ? B_SLOT : 0);
            if (helper || (q == 1 && (t == short_t || t == 0))) {
#pragma unroll 1
              for (int i = 0; i < NB; i++) {
                mbar_spin(sb + BAR_BEMPTY + bempty_off(i), par);
                expect_load_3d_e(dst + i * B_SLOT, &mw, sb + BAR_BFULL + i * 8, 0, krow + i * 32, j * 4);
                PROF_SKEW(t * 32 + q * 8 + i);
              }
            } else {
#pragma unroll
              for (int i = 0; i < NB; i++) {
                mbar_spin(sb + BAR_BEMPTY + (late && i < 7 ? bempty_off(i + 1) : bempty_off(i)), par);
                paced_load_3d_e(dst + i * B_SLOT, &mw, sb + BAR_BFULL + i * 8, 0, krow + i * 32, j * 4);
                PROF_SKEW(t * 32 + q * 8 + i);
              }
            }
          }
          par ^= 1;
        }
        if (helper || ++l == kLayers) l = 0;
      }
    } else if (warp <= 2) {
      const int w = warp - 1;
      const uint32_t abase = sb + OFF_A + w * NA * A_SLOT;
      const uint32_t fullb = sb + BAR_AFULL + w * NA * 8;
      const uint32_t emptyb = sb + BAR_AEMPTY + w * NA * 8;
      const uint32_t stagedb = sb + BAR_STAGED + w * NA * 8;
      const unsigned int base = __shfl_sync(0xffffffffu, *(volatile unsigned int*)(g_flags + (bid * 2 + w) * 32), 0);
      cluster_wait();
      uint32_t epar = 0;
      uint32_t spar = 0;
      auto refill = [&](const CUtensorMap* m, int col, int row) {
#pragma unroll 1
        for (int s = 0; s < 4; s++) {
          mbar_wait(emptyb + s * 8, epar);
          expect_load_2d_e<false>(abase + s * A_SLOT, m, fullb + s * 8, col + s * 64, row);
        }
        epar ^= 1;
      };
      auto store_refill = [&](int out_row, int col, int row, bool last_read) {
#pragma unroll 1
        for (int s = 0; s < 4; s++) {
          mbar_wait(stagedb + s * 8, spar);
          fence_async_smem();
          store_2d_e<true>(&mo64, abase + s * A_SLOT, j * 256 + s * 64, out_row);
          bulk_commit();
          bulk_wait<0>();
          __syncwarp();
          mbar_wait(emptyb + s * 8, epar);
          if (last_read) expect_load_2d_e<true>(abase + s * A_SLOT, &mx64, fullb + s * 8, col + s * 64, row);
          else expect_load_2d_e<false>(abase + s * A_SLOT, &mx64, fullb + s * 8, col + s * 64, row);
        }
        spar ^= 1;
        epar ^= 1;
      };
      auto store_tile = [&](auto stream, int out_row) {
#pragma unroll 1
        for (int c = 0; c < 4; c++) {
          mbar_wait(stagedb + c * 8, spar);
          fence_async_smem();
          arrive_e(fullb + c * 8);
          store_2d_e<decltype(stream)::value>(&mo64, abase + c * A_SLOT, j * 256 + c * 64, out_row);
        }
        spar ^= 1;
        bulk_commit();
        bulk_wait<0>();
        __syncwarp();
      };
      auto refill_shared = [&](const CUtensorMap* m32, int col, int row) {
#pragma unroll 1
        for (int s = 0; s < 4; s++) {
          mbar_wait(emptyb + s * 8, epar);
          expect_load_2d_mc_e(abase + s * A_SLOT + rank * 4096, m32, fullb + s * 8, col + s * 64, row + rank * 32);
        }
        epar ^= 1;
      };
      if (helper) {
#pragma unroll 1
        for (int h = 1; h < 2 * kJobs; h++) refill_shared(&mx32, col0 + (h & 1) * 256, job_row(h >> 1) + w * 64);
      } else {
        const uint32_t xready_peer = map_cta(sb + BAR_XREADY + w * 8, rank ^ 1);
        const unsigned int* oflag = g_flags + ((grp * 4 + kgroup_col(j, 2)) * 2 + w) * 32;
        unsigned int* done_mine = g_flags + kFlagSet + (bid * 2 + w) * 32;
        const unsigned int* done_peer = g_flags + kFlagSet + ((bid ^ 2) * 2 + w) * 32;
        uint32_t nx = 0;
#pragma unroll 1
        for (int rd = 0; rd < kRounds; rd++) {
          const int xrow = (rd * kGroups + grp) * 128 + w * 64;
          if (rd == 0) {
            refill(&mx64, 256, xrow);
          } else {
            poll_flag(done_peer, base + nx);
            store_refill(xrow - kGroups * 128, (j ^ 1) * 256, xrow, rd * kLayers == short_t);
          }
          if (rd * kLayers != short_t) {
#pragma unroll 1
            for (int h = 0; h < 2; h++) refill_shared(&mx32, (kgroup_col(rd == 0 ? 0 : j, 2) + h) * 256, xrow);
          }
#pragma unroll 1
          for (int l = 1; l < kLayers; l++) {
            if (l > 1) poll_flag(done_peer, base + nx);
            store_tile(Flag<false>(), xrow);
            PROF_SVC((rd * kLayers + l - 1) * 2 + w);
            arrive_mapped_e(xready_peer);
            arrive_e(sb + BAR_PUB + w * 8);
            mbar_wait(sb + BAR_XREADY + w * 8, nx & 1);
            fence_async_global();
            refill(&mo64, (j ^ 1) * 256, xrow);
#pragma unroll 1
            for (int h = 0; h < 2; h++) {
              poll_flag(oflag + h * 64, base + nx + 1);
              fence_async_global();
              refill_shared(&mo32, (kgroup_col(j, 2) + h) * 256, xrow);
            }
            if (rank) {
#pragma unroll 1
              for (int s = 0; s < 4; s++) mbar_wait(fullb + s * 8, 1);
            }
            nx++;
            if ((tid & 31) == 0) st_relaxed(done_mine, base + (nx == kRounds * (kLayers - 1) ? kEpoch : nx));
            __syncwarp();
          }
          const int nrow = xrow + kGroups * 128;
          if (rd + 1 == kRounds) {
            poll_flag(done_peer, base + nx);
            store_tile(Flag<true>(), xrow);
          } else {
            refill(&mx64, j * 256, nrow);
          }
          PROF_SVC((rd * kLayers + kLayers - 1) * 2 + w);
        }
      }
    } else {
      const int lane = tid & 31;
      unsigned int* myflag = g_flags + bid * 2 * 32;
      if (lane == 0) { prefetch_map(&mx32); prefetch_map(&mo64); prefetch_map(&mo32); }
      const unsigned int base = *(volatile unsigned int*)myflag;
      auto publish = [&](uint32_t n, uint32_t value) {
#pragma unroll 1
        for (int w = 0; w < 2; w++) {
          mbar_wait(sb + BAR_PUB + w * 8, n & 1);
          asm volatile("fence.acq_rel.gpu;" ::: "memory");
          if (lane == 0) st_relaxed(myflag + w * 32, base + value);
          __syncwarp();
        }
      };
      if (helper) {
        cluster_wait();
#pragma unroll 1
        for (int n = 0; n < kJobs; n++) {
          if (n + 2 < kJobs) {
            const int row = job_row(n + 2);
#pragma unroll 1
            for (int i = 0; i < 8; i++) prefetch_2d_e(&mx64, col0 + rank * 256 + (i & 3) * 64, row + (i >> 2) * 64);
          }
          publish(n, n + 1);
        }
      } else {
        {
          float c[8];
#pragma unroll
          for (int i = 0; i < 8; i++) c[i] = 0.f;
#pragma unroll 1
          for (int l = 0; l < kLayers; l++) {
            const uint4 v = *reinterpret_cast<const uint4*>(bias + l * kDim + j * 256 + lane * 8);
            const uint32_t u[4] = {v.x, v.y, v.z, v.w};
#pragma unroll
            for (int i = 0; i < 4; i++) {
              c[2 * i] += __uint_as_float(u[i] << 16) + kTrunc;
              c[2 * i + 1] += __uint_as_float(u[i] & 0xffff0000u) + kTrunc;
              uint32_t pk;
              asm("cvt.rn.bf16x2.f32 %0, %1, %2;" : "=r"(pk) : "f"(c[2 * i + 1]), "f"(c[2 * i]));
              asm volatile("st.shared.u32 [%0], %1;" ::"r"(sb + OFF_BIAS + l * 512 + (lane >> 2) * 64 + i * 16 + (lane & 3) * 4),
                           "r"(pk) : "memory");
            }
          }
#pragma unroll
          for (int i = 0; i < 15; i++) {
            const uint32_t one = (lane >> 3) == (lane & 3) ? 0x3f80u << ((lane & 4) * 4) : 0u;
            asm volatile("st.shared.u32 [%0], %1;" ::"r"(sb + OFF_UNIT + i * 128 + lane * 4), "r"(i == 7 ? one : 0u) : "memory");
          }
          fence_async_smem();
          mbar_arrive(sb + BAR_BIAS);
        }
        const __nv_bfloat16* wslice = wptr + bid * 8192;
        prefetch_1d_e(wslice + kDim * kDim, 16384);
        cluster_wait();
        uint32_t nx = 0;
#pragma unroll 1
        for (int rd = 0; rd < kRounds; rd++) {
#pragma unroll 1
          for (int l = 1; l < kLayers; l++) {
            publish(nx, nx + 1 == kRounds * (kLayers - 1) ? kEpoch : nx + 1);
            nx++;
            if (l < kLayers - 1) {
              if (rd == 0) prefetch_1d_e(wslice + (l + 1) * kDim * kDim, 16384);
            } else if (rd + 1 < kRounds) {
              const int nrow = ((rd + 1) * kGroups + grp) * 128;
#pragma unroll 1
              for (int i = 0; i < 8; i++) {
                prefetch_2d_e(&mx64, j * 256 + (i >> 1) * 64, nrow + (i & 1) * 64);
                __nanosleep(300);
              }
              if ((rd + 1) * kLayers == short_t) {
                poll_flag(g_flags + ((4 * kGroups + j) * 2 + 1) * 32, base + job_of_group(grp) + 1);
                fence_async_global();
                constexpr uint32_t order = 0x76325140;
#pragma unroll 1
                for (int i = NP; i < 8; i++)
                  prefetch_2d_e(&mp, j * 256 + ((order >> (i * 4)) & 3) * 64, nrow + ((order >> (i * 4)) & 4) * 16);
#pragma unroll 1
                for (int i = 0; i < 8; i++) {
                  if (i >= NP) mbar_wait(sb + BAR_PFREE + (i - NP) * 8, 0);
                  PROF(776 + i);
                  expect_load_2d_e<true>(sb + OFF_P + (i % NP) * A_SLOT, &mp, sb + BAR_PFULL + i * 8,
                                         j * 256 + ((order >> (i * 4)) & 3) * 64, nrow + ((order >> (i * 4)) & 4) * 16);
                }
              }
            }
          }
        }
      }
    }
    if (warp == (helper ? 3 : 2) && (tid & 31) == 0) PROF_ENDS(1002);
    if (warp == 2) PROF_DUMP();
  } else {
    asm volatile("setmaxnreg.inc.sync.aligned.u32 232;");
    const int lane = tid & 31;
    const int wtid = tid & 127;
    const uint32_t abase = sb + OFF_A + wg * NA * A_SLOT;
    const uint32_t afull = sb + BAR_AFULL + wg * NA * 8;
    const uint32_t rel = map_cta(sb + (wtid == 64 ? BAR_BEMPTY : BAR_AEMPTY + wg * NA * 8), wtid == 32 ? (rank ^ 1) : rank);
    const bool rel_b = wtid == 64;
    const bool rel_ab = (wtid & 31) == 0 && wtid < 96;
    const uint32_t frag0 = __shfl_sync(0xffffffffu, abase + ((wtid >> 5) * 16 + ((lane >> 3) & 1) * 8 + (lane & 7)) * 128 +
                                                        (((lane >> 4) ^ (lane & 7)) << 4), lane);
    const uint64_t adesc0 = desc(((abase & 0x3FFFF) >> 4) | DESC_A_LBO);
    const uint64_t bdesc0 = desc((((sb + OFF_B) & 0x3FFFF) >> 4) | DESC_B_LBO);

    const uint64_t zero = gridDim.y - 1;
    uint64_t adesc_q = adesc0 + zero, bdesc_q = bdesc0 + zero;

    float acc[128];
    uint32_t xr[64];
#pragma unroll
    for (int i = 0; i < 128; i++) acc[i] = kOffset;
#pragma unroll
    for (int i = 0; i < 64; i++) xr[i] = 0;
    int l = 0;
    bool hold = false;
    bool swap = false;
    bool brief = helper;
    int capture_q = helper ? -1 : j;

    auto release = [&](int i, bool with_a) {
      mbar_arrive_mapped_if(rel + bempty_off(i), (i & 1) ? with_a : rel_b);
    };
    auto chunk_staged = [&](int c) {
      __syncwarp();
      arrive_e(sb + BAR_STAGED + (wg * NA + c) * 8);
    };
    auto capture_slot = [&](int p) {
#pragma unroll
      for (int g = 0; g < 4; g++) ldsm4(&xr[(p * 4 + g) * 4], (frag0 ^ (g * 32)) + p * A_SLOT);
    };
    auto swap_half = [&](int p, int half) {
#pragma unroll
      for (int g = half * 2; g < half * 2 + 2; g++) {
        const uint32_t addr = (frag0 ^ (g * 32)) + p * A_SLOT;
        uint32_t n[4];
        ldsm4(n, addr);
        stsm4(addr, &xr[(p * 4 + g) * 4]);
#pragma unroll
        for (int i = 0; i < 4; i++) xr[(p * 4 + g) * 4 + i] = n[i];
      }
      if (half) chunk_staged(p);
    };
    auto chunk_of = [&](int c) { return wg ? (0x7631 >> (c * 4)) & 7 : (0x5420 >> (c * 4)) & 7; };
    auto add_partial = [&](int c) __attribute__((always_inline)) {
      const int n = chunk_of(c);
      const int slot = wg ? (0x1001 >> (c * 4)) & 3 : (0x2120 >> (c * 4)) & 3;
      PROF(768 + wg * 16 + c * 2);
      mbar_spin(sb + BAR_PFULL + n * 8, 0);
      PROF(768 + wg * 16 + c * 2 + 1);
      wg_fence();
      wgmma_n256(acc, ((uint64_t)(128 >> 4) << 32) | ((128 >> 4) << 16) | (((sb + OFF_UNIT + (6 - 2 * c) * 128) & 0x3FFFF) >> 4),
                 ((uint64_t)(256 >> 4) << 32) | ((128 >> 4) << 16) | (((sb + OFF_P + slot * A_SLOT) & 0x3FFFF) >> 4));
    };
    auto issue = [&](int i, uint32_t par, int t, bool wait_b) __attribute__((always_inline)) {
      if (!(i & 1)) mbar_spin(afull + (i >> 1) * 8, par);
      if (wait_b) mbar_spin(sb + BAR_BFULL + i * 8, i == 0 ? (par ^ t ^ 1) & 1 : par);
      const uint64_t adesc = adesc_q + ((i >> 1) * (A_SLOT >> 4) + (i & 1) * 4);
      const uint64_t bdesc = bdesc_q + i * (B_SLOT >> 4);
      wg_fence();
      wgmma_n256(acc, adesc, bdesc);
      wgmma_n256(acc, adesc + 2, bdesc + 128);
      wg_commit();
      if (i == NB - 1) { adesc_q += zero; bdesc_q += zero; }
    };
    auto retire = [&](int i, bool with_a) {
      wg_wait<2>();
      release((i + 6) & 7, with_a);
    };
    auto k_loop = [&](auto first, int t) __attribute__((always_inline)) {
      constexpr bool FIRST = decltype(first)::value;
      const bool inject = FIRST && brief && !helper;
      const uint32_t up = moves_up(t) ? B_SLOT >> 4 : 0;
      auto extras = [&](int q, int i, bool swap_now) __attribute__((always_inline)) {
        if (!FIRST) return;
        if (swap_now) swap_half(((i + 5) >> 1) & 3, (i + 1) & 1);
        if ((i & 1) && q == capture_q) capture_slot(i >> 1);
      };
      auto free_partial = [&](int c) {
        if (FIRST) mbar_arrive_if(sb + BAR_PFREE + chunk_of(c) * 8, inject && rel_b);
      };
#pragma unroll
      for (int i = 1; i < 8; i++) {
        if (!(i & 1)) PROF(t * 32 + wg * 16 + 8 + (i >> 1));
        if ((i == 1 || i == 7) && inject) add_partial(i >> 2);
        issue(i, 0, t, true);
        if (i >= 2) retire(i, rel_ab);
        if (i == 3) free_partial(0);
        extras(0, i, i >= 3 && swap);
      }
      PROF(t * 32 + wg * 16 + 1);
      if (!FIRST || !brief) {
#pragma unroll 1
        for (int q = 1; q < 3; q++) {
#pragma unroll
          for (int i = 0; i < 8; i++) {
            issue(i, q & 1, t, true);
            if (i == 0) PROF(t * 32 + wg * 16 + 3 + q);
            retire(i, rel_ab);
            extras(q, i, i < 3 && swap);
          }
          if (FIRST) swap = false;
          if (q == 1) bdesc_q += up;
        }
      }
      const bool rel_last = rel_b | (hold & rel_ab);
      auto with_a = [&](int slot) { return slot == 7 ? rel_ab : rel_last; };
      constexpr int JOIN = DRAIN + 2;
      constexpr int INJ = JOIN < 3 ? 3 : JOIN;
#pragma unroll
      for (int i = 0; i < DRAIN; i++) {
        issue(i, 1, t, true);
        retire(i, with_a((i + 6) & 7));
        if (i == 1) free_partial(1);
        extras(3, i, i < 3 && swap);
      }
      if (wg == 1) {
        mbar_spin(sb + BAR_BFULL + DRAIN * 8, 1);
        wg_wait<1>();
        release((DRAIN + 6) & 7, with_a((DRAIN + 6) & 7));
        wg_wait<0>();
        release((DRAIN + 7) & 7, with_a((DRAIN + 7) & 7));
        if (DRAIN < 2) free_partial(1);
        PROF(t * 32 + wg * 16 + 12);
#pragma unroll
        for (int i = DRAIN; i < 3; i++) extras(-2, i, swap);
        mbar_spin(sb + BAR_ORDER, t & 1);
        PROF(t * 32 + wg * 16 + 6);
#pragma unroll
        for (int i = DRAIN; i < JOIN; i++) {
          issue(i, 1, t, i != DRAIN);
          extras(3, i, false);
        }
      } else {
        PROF(t * 32 + wg * 16 + 6);
#pragma unroll
        for (int i = DRAIN; i < JOIN; i++) {
          issue(i, 1, t, true);
          retire(i, with_a((i + 6) & 7));
          if (i == 1) free_partial(1);
          extras(3, i, i < 3 && swap);
        }
      }
#pragma unroll
      for (int i = JOIN; i < 8; i++) {
        if ((i == INJ || i == 7) && inject) add_partial(i == INJ ? 2 : 3);
        issue(i, 1, t, true);
        if (i == DCN_ORD) mbar_arrive_if(sb + BAR_ORDER, rel_b & (wg == 0));
        retire(i, rel_last);
        if (i == INJ + 2) free_partial(2);
        extras(3, i, false);
      }
      bdesc_q -= up;
    };

    cluster_wait();
    const int ntiles = helper ? kJobs : kTiles;
    mbar_spin(sb + BAR_BFULL0, 0);
    issue(0, 0, 0, false);
#pragma unroll 1
    for (int t = 0;; t++) {
      hold = (helper || l == kLayers - 1) && (t + 1 < ntiles);
      PROF(t * 32 + wg * 16 + 0);
      if (l == 0) k_loop(Flag<true>(), t);
      else k_loop(Flag<false>(), t);
      if (t == 0 && !helper) mbar_spin(sb + BAR_BIAS, 0);
      const uint32_t bl = sb + OFF_BIAS + l * 512 + ((frag0 >> 3) & 0x30);
      uint32_t bq[8][4];
      auto load_bias = [&](int U) {
        asm volatile("ld.shared.v4.u32 {%0, %1, %2, %3}, [%4];"
                     : "=r"(bq[U][0]), "=r"(bq[U][1]), "=r"(bq[U][2]), "=r"(bq[U][3]) : "r"(bl + U * 64));
      };
#pragma unroll
      for (int U = 0; U < BPRE; U++) load_bias(U);
      uint32_t fa[4];
#pragma unroll
      for (int g = 0; g < 4; g++) asm volatile("xor.b32 %0, %1, %2;" : "=r"(fa[g]) : "r"(frag0), "r"(g * 32));
      wg_wait<1>();
      release(6, false);
      if (t + 1 < ntiles) mbar_spin(sb + BAR_BFULL0, (t + 1) & 1);
      wg_wait<0>();
#pragma unroll
      for (int i = 0; i < 128; i++) asm volatile("" : "+f"(acc[i]) :: "memory");
      release(7, rel_b | (hold & rel_ab));
      PROF(t * 32 + wg * 16 + 2);

      auto pack = [&](int i, float off) {
        uint32_t v;
        asm("cvt.rn.bf16x2.f32 %0, %1, %2;" : "=r"(v) : "f"(acc[i * 2 + 1] - off), "f"(acc[i * 2] - off));
        return v;
      };
      auto cross = [&](int T, int i, float off) {
        uint32_t s2 = pack(T * 4 + i, off), o;
        asm("add.rn.bf16x2 %0, %1, %2;" : "=r"(s2) : "r"(s2), "r"(bq[T >> 1][(T & 1) * 2 + (i >> 1)]));
        asm("fma.rn.bf16x2 %0, %1, %2, %1;" : "=r"(o) : "r"(xr[T * 4 + i]), "r"(s2));
        return o;
      };
      auto reset = [&](int T) {
#pragma unroll
        for (int i = T * 8; i < T * 8 + 8; i += 4)
          asm volatile("ld.volatile.shared.v4.f32 {%0, %1, %2, %3}, [%4];"
                       : "+f"(acc[i]), "+f"(acc[i + 1]), "+f"(acc[i + 2]), "+f"(acc[i + 3]) : "r"(sb + OFF_INIT));
      };
      auto offset_for = [&](int T) { return T >= LAG ? acc[(T - LAG) * 8 + 7] : kOffset; };
      if (helper) {
        uint32_t id;
        asm volatile("mov.u32 %0, %%tid.x;" : "=r"(id));
        __nv_bfloat16* dst = optr + (size_t)(job_row(t) + wg * 64) * kDim + j * 256 + (id & 127) * 2;
        uint64_t pol;
        asm volatile("createpolicy.fractional.L2::evict_first.b64 %0, 1.0;" : "=l"(pol));
#pragma unroll
        for (int T = 0; T < 16; T++) {
#pragma unroll
          for (int i = 0; i < 4; i++)
            asm volatile("st.global.L2::cache_hint.b32 [%0], %1, %2;"
                         ::"l"(dst + (T * 4 + (i ^ 1)) * kDim), "r"(pack(T * 4 + i, offset_for(T))), "l"(pol) : "memory");
          reset(T);
        }
        asm volatile("bar.sync %0, 128;" ::"r"(wg + 1) : "memory");
        mbar_arrive_if(sb + BAR_PUB + wg * 8, rel_b);
      } else if (hold) {
#pragma unroll
        for (int T = 0; T < 16; T++) {
#pragma unroll
          for (int i = 0; i < 4; i++) xr[T * 4 + i] = cross(T, i, offset_for(T));
          if ((T & 1) && (T >> 1) + BPRE < 8) load_bias((T >> 1) + BPRE);
          reset(T);
        }
      } else {
        uint32_t o[16][4];
#pragma unroll
        for (int T = 0; T < 16; T++) {
          float off = kOffset;
          if (DCN_ELAG && T >= DCN_ELAG)
            asm("lop3.b32 %0, %1, %2, %3, 0xea;" : "=f"(off) : "r"(o[T - DCN_ELAG][3]), "r"((uint32_t)zero), "f"(kOffset));
#pragma unroll
          for (int i = 0; i < 4; i++) o[T][i] = cross(T, i, off);
          stsm4(fa[T & 3] + (T >> 2) * A_SLOT, o[T]);
          if ((T & 3) == 3) chunk_staged(T >> 2);
          if ((T & 1) && (T >> 1) + BPRE < 8) load_bias((T >> 1) + BPRE);
        }
        PROF(t * 32 + wg * 16 + 7);
      }
      PROF(t * 32 + wg * 16 + 3);
      if (t + 1 == ntiles) break;
      issue(0, 0, 0, false);
      if (helper || ++l == kLayers) l = 0;
      swap = hold && !helper;
      brief = helper || t + 1 == short_t;
      capture_q = -1;
    }
  }
}

__global__ void __launch_bounds__(256) dcn_fallback(const __nv_bfloat16* __restrict__ x0, const __nv_bfloat16* __restrict__ w,
                                                    const __nv_bfloat16* __restrict__ b, __nv_bfloat16* __restrict__ out) {
  __shared__ float xs[8][kDim];
  const size_t r0 = (size_t)blockIdx.x * 8;
  for (int i = threadIdx.x; i < 8 * kDim; i += 256) xs[i / kDim][i % kDim] = __bfloat162float(x0[r0 * kDim + i]);
  __syncthreads();
  for (int l = 0; l < kLayers; l++) {
    float a[4][8] = {};
    for (int k = 0; k < kDim; k++) {
#pragma unroll
      for (int c = 0; c < 4; c++) {
        const float wv = __bfloat162float(w[((size_t)l * kDim + k) * kDim + c * 256 + threadIdx.x]);
#pragma unroll
        for (int r = 0; r < 8; r++) a[c][r] += xs[r][k] * wv;
      }
    }
    __syncthreads();
#pragma unroll
    for (int c = 0; c < 4; c++) {
      const int n = c * 256 + threadIdx.x;
#pragma unroll
      for (int r = 0; r < 8; r++) {
        const float v = __bfloat162float(x0[(r0 + r) * kDim + n]) * (a[c][r] + __bfloat162float(b[l * kDim + n])) + xs[r][n];
        xs[r][n] = __bfloat162float(__float2bfloat16(v));
      }
    }
    __syncthreads();
  }
  for (int i = threadIdx.x; i < 8 * kDim; i += 256) out[r0 * kDim + i] = __float2bfloat16(xs[i / kDim][i % kDim]);
}

typedef CUresult (*EncodeFn)(CUtensorMap*, CUtensorMapDataType, cuuint32_t, void*, const cuuint64_t*, const cuuint64_t*,
                             const cuuint32_t*, const cuuint32_t*, CUtensorMapInterleave, CUtensorMapSwizzle,
                             CUtensorMapL2promotion, CUtensorMapFloatOOBfill);

static void make_map_2d(EncodeFn enc, CUtensorMap* m, void* ptr, uint64_t rows, uint32_t box_rows,
                        CUtensorMapSwizzle swizzle = CU_TENSOR_MAP_SWIZZLE_128B) {
  cuuint64_t dims[2] = {(cuuint64_t)kDim, rows};
  cuuint64_t strides[1] = {kDim * 2};
  cuuint32_t box[2] = {64, box_rows};
  cuuint32_t es[2] = {1, 1};
  enc(m, CU_TENSOR_MAP_DATA_TYPE_BFLOAT16, 2, ptr, dims, strides, box, es, CU_TENSOR_MAP_INTERLEAVE_NONE,
      swizzle, CU_TENSOR_MAP_L2_PROMOTION_L2_128B, CU_TENSOR_MAP_FLOAT_OOB_FILL_NONE);
}

}

extern "C" void kernel_launch(void* const* d_in, const int* in_sizes, int n_in, void* d_out, int out_size) {
  using namespace dcn;
  (void)in_sizes; (void)n_in; (void)out_size;
  void* fn = nullptr;
  cudaDriverEntryPointQueryResult qr;
  cudaGetDriverEntryPoint("cuTensorMapEncodeTiled", &fn, cudaEnableDefault, &qr);
  EncodeFn enc = (EncodeFn)fn;
  CUtensorMap mx64, mx32, mo64, mo32, mw, mp;
  make_map_2d(enc, &mx64, d_in[0], kRows, 64);
  make_map_2d(enc, &mx32, d_in[0], kRows, 32);
  make_map_2d(enc, &mo64, d_out, kRows, 64);
  make_map_2d(enc, &mo32, d_out, kRows, 32);
  make_map_2d(enc, &mp, d_out, kRows, 64, CU_TENSOR_MAP_SWIZZLE_NONE);
  {
    cuuint64_t dims[3] = {64, (cuuint64_t)kLayers * kDim, kDim / 64};
    cuuint64_t strides[2] = {kDim * 2, 128};
    cuuint32_t box[3] = {64, 32, 4};
    cuuint32_t es[3] = {1, 1, 1};
    enc(&mw, CU_TENSOR_MAP_DATA_TYPE_BFLOAT16, 3, d_in[1], dims, strides, box, es, CU_TENSOR_MAP_INTERLEAVE_NONE,
        CU_TENSOR_MAP_SWIZZLE_128B, CU_TENSOR_MAP_L2_PROMOTION_L2_128B, CU_TENSOR_MAP_FLOAT_OOB_FILL_NONE);
  }
  const __nv_bfloat16* x0 = (const __nv_bfloat16*)d_in[0];
  const __nv_bfloat16* w = (const __nv_bfloat16*)d_in[1];
  const __nv_bfloat16* b = (const __nv_bfloat16*)d_in[2];
  __nv_bfloat16* out = (__nv_bfloat16*)d_out;
  constexpr int smem = SMEM_BYTES + PROF_SMEM;
  cudaFuncSetAttribute(dcn_kernel, cudaFuncAttributeMaxDynamicSharedMemorySize, smem);

  cudaLaunchConfig_t cfg = {};
  cfg.gridDim = dim3(4 * kGroups + 4);
  cfg.blockDim = dim3(384);
  cfg.dynamicSmemBytes = smem;
  cudaLaunchAttribute attr;
  attr.id = cudaLaunchAttributeClusterDimension;
  attr.val.clusterDim.x = 2;
  attr.val.clusterDim.y = 1;
  attr.val.clusterDim.z = 1;
  cfg.attrs = &attr;
  cfg.numAttrs = 1;
  int clusters = 0;
  cudaOccupancyMaxActiveClusters(&clusters, dcn_kernel, &cfg);
  if (clusters >= 2 * kGroups) {
    const int grid = 4 * kGroups + (clusters >= 2 * kGroups + 2 ? 4 : 0);
    dcn_kernel<<<grid, 384, smem>>>(mx64, mx32, mo64, mo32, mw, mp, x0, w, b, out);
  } else {
    dcn_fallback<<<kRows / 8, 256>>>(x0, w, b, out);
  }
}
```

```cpp
#include <cuda_runtime.h>
#include <cuda.h>
#include <cuda_bf16.h>
#include <stdint.h>

namespace dcn {

__device__ __forceinline__ void wgmma_n256(float (&d)[128], uint64_t da, uint64_t db) {
  asm volatile("wgmma.mma_async.sync.aligned.m64n256k16.f32.bf16.bf16 "
    "{%0, %1, %2, %3, %4, %5, %6, %7, %8, %9, %10, %11, %12, %13, %14, %15, %16, %17, %18, %19, %20, %21, %22, %23, %24, %25, %26, %27, %28, %29, %30, %31, %32, %33, %34, %35, %36, %37, %38, %39, %40, %41, %42, %43, %44, %45, %46, %47, %48, %49, %50, %51, %52, %53, %54, %55, %56, %57, %58, %59, %60, %61, %62, %63, %64, %65, %66, %67, %68, %69, %70, %71, %72, %73, %74, %75, %76, %77, %78, %79, %80, %81, %82, %83, %84, %85, %86, %87, %88, %89, %90, %91, %92, %93, %94, %95, %96, %97, %98, %99, %100, %101, %102, %103, %104, %105, %106, %107, %108, %109, %110, %111, %112, %113, %114, %115, %116, %117, %118, %119, %120, %121, %122, %123, %124, %125, %126, %127}, "
    "%128, %129, 1, 1, 1, 0, 1;\n"
    : "+f"(d[0]), "+f"(d[1]), "+f"(d[2]), "+f"(d[3]), "+f"(d[4]), "+f"(d[5]), "+f"(d[6]), "+f"(d[7]), "+f"(d[8]), "+f"(d[9]), "+f"(d[10]), "+f"(d[11]), "+f"(d[12]), "+f"(d[13]), "+f"(d[14]), "+f"(d[15]), "+f"(d[16]), "+f"(d[17]), "+f"(d[18]), "+f"(d[19]), "+f"(d[20]), "+f"(d[21]), "+f"(d[22]), "+f"(d[23]), "+f"(d[24]), "+f"(d[25]), "+f"(d[26]), "+f"(d[27]), "+f"(d[28]), "+f"(d[29]), "+f"(d[30]), "+f"(d[31]), "+f"(d[32]), "+f"(d[33]), "+f"(d[34]), "+f"(d[35]), "+f"(d[36]), "+f"(d[37]), "+f"(d[38]), "+f"(d[39]), "+f"(d[40]), "+f"(d[41]), "+f"(d[42]), "+f"(d[43]), "+f"(d[44]), "+f"(d[45]), "+f"(d[46]), "+f"(d[47]), "+f"(d[48]), "+f"(d[49]), "+f"(d[50]), "+f"(d[51]), "+f"(d[52]), "+f"(d[53]), "+f"(d[54]), "+f"(d[55]), "+f"(d[56]), "+f"(d[57]), "+f"(d[58]), "+f"(d[59]), "+f"(d[60]), "+f"(d[61]), "+f"(d[62]), "+f"(d[63]), "+f"(d[64]), "+f"(d[65]), "+f"(d[66]), "+f"(d[67]), "+f"(d[68]), "+f"(d[69]), "+f"(d[70]), "+f"(d[71]), "+f"(d[72]), "+f"(d[73]), "+f"(d[74]), "+f"(d[75]), "+f"(d[76]), "+f"(d[77]), "+f"(d[78]), "+f"(d[79]), "+f"(d[80]), "+f"(d[81]), "+f"(d[82]), "+f"(d[83]), "+f"(d[84]), "+f"(d[85]), "+f"(d[86]), "+f"(d[87]), "+f"(d[88]), "+f"(d[89]), "+f"(d[90]), "+f"(d[91]), "+f"(d[92]), "+f"(d[93]), "+f"(d[94]), "+f"(d[95]), "+f"(d[96]), "+f"(d[97]), "+f"(d[98]), "+f"(d[99]), "+f"(d[100]), "+f"(d[101]), "+f"(d[102]), "+f"(d[103]), "+f"(d[104]), "+f"(d[105]), "+f"(d[106]), "+f"(d[107]), "+f"(d[108]), "+f"(d[109]), "+f"(d[110]), "+f"(d[111]), "+f"(d[112]), "+f"(d[113]), "+f"(d[114]), "+f"(d[115]), "+f"(d[116]), "+f"(d[117]), "+f"(d[118]), "+f"(d[119]), "+f"(d[120]), "+f"(d[121]), "+f"(d[122]), "+f"(d[123]), "+f"(d[124]), "+f"(d[125]), "+f"(d[126]), "+f"(d[127])
    : "l"(da), "l"(db));
}

constexpr int kDim = 1024;
constexpr int kRows = 16384;
constexpr int kLayers = 6;
constexpr int kGroups = 32;
constexpr int kRounds = kRows / 128 / kGroups;
constexpr int kTiles = kRounds * kLayers;

constexpr int kJobs = kGroups;
constexpr int kEpoch = 32;
constexpr int NA = 4;
constexpr int NB = 8;
#define DCN_OFF 85.333336f
constexpr float kOffset = DCN_OFF;
constexpr float kTrunc = 64 * 0.375f / 131072;
#define DCN_DRAIN 1
#define DCN_LAG 3
constexpr int DRAIN = DCN_DRAIN;
constexpr int LAG = DCN_LAG;
#define DCN_NF 2
#define DCN_T0 0
#define DCN_W1 0
#define DCN_BPRE 5
#define DCN_HPRE 6
constexpr int HPRE = DCN_HPRE;
constexpr int BPRE = DCN_BPRE;
constexpr int A_SLOT = 8192;
constexpr int B_SLOT = 16384;
constexpr int OFF_B = 0;
constexpr int NP = 3;
constexpr int OFF_P = OFF_B + NB * B_SLOT;
constexpr int OFF_A = OFF_P + NP * A_SLOT;
constexpr int OFF_UNIT = OFF_A + 2 * NA * A_SLOT;
constexpr int OFF_BIAS = OFF_UNIT + 2048;
constexpr int OFF_INIT = OFF_BIAS + kLayers * 256 * 2;
constexpr int OFF_BAR = OFF_INIT + 16;
constexpr int BAR_BFULL = OFF_BAR;
constexpr int BAR_BFULL0 = BAR_BFULL + NB * 8;
constexpr int BAR_BEMPTY = BAR_BFULL0 + 8;
constexpr int BAR_AFULL = BAR_BEMPTY + NB * 8;
constexpr int BAR_AEMPTY = BAR_AFULL + 2 * NA * 8;
constexpr int BAR_XREADY = BAR_AEMPTY + 2 * NA * 8;
constexpr int BAR_PUB = BAR_XREADY + 16;
constexpr int BAR_PFULL = BAR_PUB + 16;
constexpr int BAR_PFREE = BAR_PFULL + 8 * 8;
constexpr int BAR_STAGED = BAR_PFREE + 8 * 8;
constexpr int BAR_ORDER = BAR_STAGED + 2 * NA * 8;
constexpr int BAR_BIAS = BAR_ORDER + 8;
constexpr int SMEM_BYTES = BAR_BIAS + 8;
static_assert(SMEM_BYTES <= 232448, "shared memory budget");

constexpr int kFlagSet = 4 * (kGroups + 1) * 2 * 32;
__device__ unsigned int g_flags[2 * kFlagSet];

__device__ __forceinline__ uint32_t smem_u32(const void* p) { return (uint32_t)__cvta_generic_to_shared(p); }
__device__ __forceinline__ void mbar_init(uint32_t bar, int cnt) {
  asm volatile("mbarrier.init.shared::cta.b64 [%0], %1;" ::"r"(bar), "r"(cnt) : "memory");
}
__device__ __forceinline__ void mbar_arrive(uint32_t bar) {
  asm volatile("mbarrier.arrive.shared::cta.b64 _, [%0];" ::"r"(bar) : "memory");
}
__device__ __forceinline__ uint32_t map_cta(uint32_t addr, uint32_t cta) {
  uint32_t r;
  asm volatile("mapa.shared::cluster.u32 %0, %1, %2;" : "=r"(r) : "r"(addr), "r"(cta));
  return r;
}
__device__ __forceinline__ void mbar_arrive_mapped(uint32_t cluster_addr) {
  asm volatile("mbarrier.arrive.shared::cluster.b64 _, [%0];" ::"r"(cluster_addr) : "memory");
}
__device__ __forceinline__ void mbar_arrive_mapped_if(uint32_t cluster_addr, bool pred) {
  asm volatile("{\n.reg .pred p;\nsetp.ne.u32 p, %1, 0;\n@p mbarrier.arrive.shared::cluster.b64 _, [%0];\n}"
               ::"r"(cluster_addr), "r"((uint32_t)pred) : "memory");
}
__device__ __forceinline__ void mbar_arrive_if(uint32_t bar, bool pred) {
  asm volatile("{\n.reg .pred p;\nsetp.ne.u32 p, %1, 0;\n@p mbarrier.arrive.shared::cta.b64 _, [%0];\n}"
               ::"r"(bar), "r"((uint32_t)pred) : "memory");
}
__device__ __forceinline__ void mbar_wait(uint32_t bar, uint32_t parity) {
  asm volatile(
      "{\n.reg .pred p;\n.reg .u32 c;\n"
      "mbarrier.try_wait.parity.shared::cta.b64 p, [%0], %1;\n"
      "@p bra DONE;\n"
      "mov.u32 c, 0;\n"
      "LOOP:\n"
      "mbarrier.try_wait.parity.shared::cta.b64 p, [%0], %1;\n"
      "@p bra DONE;\n"
      "add.u32 c, c, 1;\n"
      "setp.lt.u32 p, c, 1048576;\n"
      "@p bra LOOP;\n"
      "trap;\n"
      "DONE:\n}"
      ::"r"(bar), "r"(parity) : "memory");
}
__device__ __forceinline__ void mbar_spin(uint32_t bar, uint32_t parity) {
  asm volatile(
      "{\n.reg .pred p;\n"
      "LOOP:\n"
      "mbarrier.try_wait.parity.shared::cta.b64 p, [%0], %1;\n"
      "@!p bra LOOP;\n}"
      ::"r"(bar), "r"(parity) : "memory");
}
#define ELECT_BEGIN "{\n.reg .pred e;\nelect.sync _|e, 0xffffffff;\n"
template <bool STREAM> __device__ __forceinline__ void expect_load_2d_e(uint32_t dst, const CUtensorMap* m, uint32_t bar, int c0, int c1) {
  if (STREAM) {
    asm volatile(ELECT_BEGIN ".reg .b64 pol;\ncreatepolicy.fractional.L2::evict_first.b64 pol, 1.0;\n"
                 "@e mbarrier.arrive.expect_tx.shared::cta.b64 _, [%2], 8192;\n"
                 "@e cp.async.bulk.tensor.2d.shared::cluster.global.mbarrier::complete_tx::bytes.L2::cache_hint [%0], [%1, {%3, %4}], [%2], pol;\n}"
                 ::"r"(dst), "l"(m), "r"(bar), "r"(c0), "r"(c1) : "memory");
  } else {
    asm volatile(ELECT_BEGIN
                 "@e mbarrier.arrive.expect_tx.shared::cta.b64 _, [%2], 8192;\n"
                 "@e cp.async.bulk.tensor.2d.shared::cluster.global.mbarrier::complete_tx::bytes [%0], [%1, {%3, %4}], [%2];\n}"
                 ::"r"(dst), "l"(m), "r"(bar), "r"(c0), "r"(c1) : "memory");
  }
}
__device__ __forceinline__ void expect_load_2d_mc_e(uint32_t dst, const CUtensorMap* m, uint32_t bar, int c0, int c1) {
  asm volatile(ELECT_BEGIN ".reg .b64 pol;\ncreatepolicy.fractional.L2::evict_first.b64 pol, 1.0;\n"
               "@e mbarrier.arrive.expect_tx.shared::cta.b64 _, [%2], 8192;\n"
               "@e cp.async.bulk.tensor.2d.shared::cluster.global.mbarrier::complete_tx::bytes.multicast::cluster.L2::cache_hint [%0], [%1, {%3, %4}], [%2], %5, pol;\n}"
               ::"r"(dst), "l"(m), "r"(bar), "r"(c0), "r"(c1), "h"((uint16_t)3) : "memory");
}
__device__ __forceinline__ void expect_load_3d_e(uint32_t dst, const CUtensorMap* m, uint32_t bar, int c0, int c1, int c2) {
  asm volatile(ELECT_BEGIN
               "@e mbarrier.arrive.expect_tx.shared::cta.b64 _, [%2], 16384;\n"
               "@e cp.async.bulk.tensor.3d.shared::cluster.global.mbarrier::complete_tx::bytes [%0], [%1, {%3, %4, %5}], [%2];\n}"
               ::"r"(dst), "l"(m), "r"(bar), "r"(c0), "r"(c1), "r"(c2) : "memory");
}
template <bool STREAM> __device__ __forceinline__ void store_2d_e(const CUtensorMap* m, uint32_t src, int c0, int c1) {
  if (STREAM) {
    asm volatile(ELECT_BEGIN ".reg .b64 pol;\ncreatepolicy.fractional.L2::evict_first.b64 pol, 1.0;\n"
                 "@e cp.async.bulk.tensor.2d.global.shared::cta.bulk_group.L2::cache_hint [%0, {%2, %3}], [%1], pol;\n}"
                 ::"l"(m), "r"(src), "r"(c0), "r"(c1) : "memory");
  } else {
    asm volatile(ELECT_BEGIN
                 "@e cp.async.bulk.tensor.2d.global.shared::cta.bulk_group [%0, {%2, %3}], [%1];\n}"
                 ::"l"(m), "r"(src), "r"(c0), "r"(c1) : "memory");
  }
}
__device__ __forceinline__ void prefetch_2d_e(const CUtensorMap* m, int c0, int c1) {
  asm volatile(ELECT_BEGIN
               "@e cp.async.bulk.prefetch.tensor.2d.L2.global [%0, {%1, %2}];\n}"
               ::"l"(m), "r"(c0), "r"(c1) : "memory");
}
__device__ __forceinline__ void prefetch_1d_e(const void* ptr, uint32_t bytes) {
  asm volatile(ELECT_BEGIN
               "@e cp.async.bulk.prefetch.L2.global [%0], %1;\n}"
               ::"l"(ptr), "r"(bytes) : "memory");
}
__device__ __forceinline__ void paced_load_3d_e(uint32_t dst, const CUtensorMap* m, uint32_t bar, int c0, int c1, int c2, bool pace) {
  asm volatile(ELECT_BEGIN ".reg .pred p;\nsetp.ne.u32 p, %6, 0;\n"
               "@e mbarrier.arrive.expect_tx.shared::cta.b64 _, [%2], 16384;\n"
               "@p nanosleep.u32 128;\n"
               "@e cp.async.bulk.tensor.3d.shared::cluster.global.mbarrier::complete_tx::bytes [%0], [%1, {%3, %4, %5}], [%2];\n}"
               ::"r"(dst), "l"(m), "r"(bar), "r"(c0), "r"(c1), "r"(c2), "r"((uint32_t)pace) : "memory");
}
__device__ __forceinline__ void arrive_mapped_e(uint32_t cluster_addr) {
  asm volatile(ELECT_BEGIN "@e mbarrier.arrive.shared::cluster.b64 _, [%0];\n}" ::"r"(cluster_addr) : "memory");
}
__device__ __forceinline__ void arrive_e(uint32_t bar) {
  asm volatile(ELECT_BEGIN "@e mbarrier.arrive.shared::cta.b64 _, [%0];\n}" ::"r"(bar) : "memory");
}
__device__ __forceinline__ void bulk_commit() { asm volatile("cp.async.bulk.commit_group;" ::: "memory"); }
template <int N> __device__ __forceinline__ void bulk_wait() { asm volatile("cp.async.bulk.wait_group %0;" ::"n"(N) : "memory"); }
__device__ __forceinline__ void wg_fence() { asm volatile("wgmma.fence.sync.aligned;" ::: "memory"); }
__device__ __forceinline__ void wg_commit() { asm volatile("wgmma.commit_group.sync.aligned;" ::: "memory"); }
template <int N> __device__ __forceinline__ void wg_wait() { asm volatile("wgmma.wait_group.sync.aligned %0;" ::"n"(N) : "memory"); }
__device__ __forceinline__ void fence_async_global() { asm volatile("fence.proxy.async.global;" ::: "memory"); }
__device__ __forceinline__ void st_relaxed(unsigned int* p, unsigned int v) {
  asm volatile("st.relaxed.gpu.global.u32 [%0], %1;" ::"l"(p), "r"(v) : "memory");
}
__device__ __forceinline__ unsigned int ld_acquire(const unsigned int* p) {
  unsigned int v;
  asm volatile("ld.acquire.gpu.global.u32 %0, [%1];" : "=r"(v) : "l"(p) : "memory");
  return v;
}
__device__ __forceinline__ void ldsm4(uint32_t* r, uint32_t addr) {
  asm volatile("ldmatrix.sync.aligned.m8n8.x4.shared.b16 {%0, %1, %2, %3}, [%4];"
               : "=r"(r[0]), "=r"(r[1]), "=r"(r[2]), "=r"(r[3]) : "r"(addr) : "memory");
}
__device__ __forceinline__ void stsm4(uint32_t addr, const uint32_t* r) {
  asm volatile("stmatrix.sync.aligned.m8n8.x4.shared.b16 [%0], {%1, %2, %3, %4};"
               ::"r"(addr), "r"(r[0]), "r"(r[1]), "r"(r[2]), "r"(r[3]) : "memory");
}
template <bool V> struct Flag { static constexpr bool value = V; };
template <int V> struct Int { static constexpr int value = V; };
__device__ __forceinline__ void fence_async_smem() { asm volatile("fence.proxy.async.shared::cta;" ::: "memory"); }
__device__ __forceinline__ void cluster_arrive_relaxed() { asm volatile("barrier.cluster.arrive.relaxed.aligned;" ::: "memory"); }
__device__ __forceinline__ void cluster_wait() { asm volatile("barrier.cluster.wait.acquire.aligned;" ::: "memory"); }
__device__ __forceinline__ void prefetch_map(const CUtensorMap* m) {
  asm volatile("prefetch.tensormap [%0];" ::"l"(m) : "memory");
}
__device__ __forceinline__ void prefetch_map_e(const CUtensorMap* m) {
  asm volatile(ELECT_BEGIN "@e prefetch.tensormap [%0];\n}" ::"l"(m) : "memory");
}
__device__ __forceinline__ void poll_flag(const unsigned int* ptr, unsigned int target) {
  asm volatile(
      "{\n.reg .pred p;\n.reg .u32 c;\n.reg .s32 v;\n"
      "mov.u32 c, 0;\n"
      "LOOP:\n"
      "ld.acquire.gpu.global.s32 v, [%0];\n"
      "sub.s32 v, v, %1;\n"
      "setp.ge.s32 p, v, 0;\n"
      "@p bra DONE;\n"
      "add.u32 c, c, 1;\n"
      "setp.lt.u32 p, c, 1048576;\n"
      "@p bra LOOP;\n"
      "trap;\n"
      "DONE:\n}"
      ::"l"(ptr), "r"(target) : "memory");
}

constexpr uint32_t DESC_HI = (1024u >> 4) | (1u << 30);
__device__ __forceinline__ uint64_t desc(uint32_t lo) { return ((uint64_t)DESC_HI << 32) | lo; }
constexpr uint32_t DESC_A_LBO = 1u << 16;
constexpr uint32_t DESC_B_LBO = (4096u >> 4) << 16;

__device__ __forceinline__ int kgroup_col(int j, int q) {
  return q == 0 ? j : (q == 1 ? (j ^ 1) : (((j ^ 2) & ~1) + (q - 2)));
}

__device__ __forceinline__ int role_of_cluster(int c) {
  const int a = c - 4;
  const int b = c - 36, r = (b * 37) >> 8;
  const int first = (a & ~7) + (a & 3) * 2 + ((a >> 2) & 1);
  const int second = 32 + r * 8 + ((0x7531640 >> (((b - r * 7) * 4) & 31)) & 7);
  return c >= 2 * kGroups ? c : (c >= 36 ? second : (c >= 4 ? first : 34 + c * 8));
}
__device__ __forceinline__ int helped_round(int grp) { return (grp & 2) ? (grp & 3) - 1 : 3; }
__device__ __forceinline__ int job_of_group(int grp) {
  return (grp & 2) ? (grp & 1) * 8 + (grp >> 2) : 16 + (grp >> 2) * 2 + (grp & 1);
}
__device__ __forceinline__ int job_row(int n) {
  const int grp = n < 16 ? (n & 7) * 4 + 2 + (n >> 3) : ((n - 16) >> 1) * 4 + (n & 1);
  return (helped_round(grp) * kGroups + grp) * 128;
}

#define PROF_ENDS(idx) do {} while (0)
#define PROF_SVC(idx) do {} while (0)
#define PROF_ST(idx) do {} while (0)
#define PROF_EPI(c) do {} while (0)
#define PROF_SKEW(idx) do {} while (0)
#define PROF(idx) do {} while (0)
#define PROF_DUMP() do {} while (0)
constexpr int PROF_SMEM = 0;

__global__ void __cluster_dims__(2, 1, 1) __launch_bounds__(384, 1)
dcn_kernel(const __nv_bfloat16* __restrict__ xptr, const __nv_bfloat16* __restrict__ wptr,
           const __nv_bfloat16* __restrict__ bias, __nv_bfloat16* optr,
           const __grid_constant__ CUtensorMap mx64, const __grid_constant__ CUtensorMap mx32,
           const __grid_constant__ CUtensorMap mo64, const __grid_constant__ CUtensorMap mo32,
           const __grid_constant__ CUtensorMap mw, const __grid_constant__ CUtensorMap mp) {
  extern __shared__ __align__(1024) uint8_t smem_raw[];
  const uint32_t sb = smem_u32(smem_raw);
  const int tid = threadIdx.x;
  if ((tid >> 5) == 8) PROF_ST(0);
  uint32_t entry;
  asm volatile("mov.u32 %0, %%clock;" : "=r"(entry));
  const int wid = __shfl_sync(0xffffffffu, tid >> 5, 0);
  if (wid == 0) {
    asm volatile("prefetch.global.L2 [%0];" ::"l"(wptr + ((blockIdx.x & 31) * 32 + tid) * 64));
    asm volatile("prefetch.global.L2 [%0];" ::"l"(xptr + ((blockIdx.x & 127) * 32 + tid) * kDim));
    prefetch_map_e(&mw);
    prefetch_map_e(&mx64);
    PROF_ST(29);
  }
  const int bid = role_of_cluster(blockIdx.x >> 1) * 2 + (blockIdx.x & 1);
  const int j = bid & 3;
  const int grp = bid >> 2;
  const bool helper = grp == kGroups;
  const int col0 = helper ? kgroup_col(j, 2) * 256 : 0;
  const int row0 = helper ? job_row(0) : grp * 128;
  auto first_loads = [&](int s) {
    const int col = col0 + s * 64;
    expect_load_3d_e(sb + OFF_B + 2 * s * B_SLOT, &mw, sb + (s ? BAR_BFULL + 2 * s * 8 : BAR_BFULL0), 0, col, j * 4);
    expect_load_2d_e<false>(sb + OFF_A + s * A_SLOT, &mx64, sb + BAR_AFULL + s * 8, col, row0);
    expect_load_3d_e(sb + OFF_B + (2 * s + 1) * B_SLOT, &mw, sb + BAR_BFULL + (2 * s + 1) * 8, 0, col + 32, j * 4);
    expect_load_2d_e<false>(sb + OFF_A + (NA + s) * A_SLOT, &mx64, sb + BAR_AFULL + (NA + s) * 8, col, row0 + 64);
    PROF_ST(2 + s);
  };
  auto init_full = [&](int s) {
    mbar_init(sb + (s ? BAR_BFULL + 2 * s * 8 : BAR_BFULL0), 1);
    mbar_init(sb + BAR_BFULL + (2 * s + 1) * 8, 1);
    mbar_init(sb + BAR_AFULL + s * 8, 1);
    mbar_init(sb + BAR_AFULL + (NA + s) * 8, 1);
  };
  if (wid == 8) {
    PROF_ST(28);
    if (tid == 256) {
      init_full(0);
      asm volatile("fence.mbarrier_init.release.cluster;" ::: "memory");
    }
    __syncwarp();
    PROF_ST(1);
    first_loads(0);
    if (tid == 256) {
#pragma unroll
      for (int s = 1; s < 4; s++) init_full(s);
      asm volatile("fence.mbarrier_init.release.cluster;" ::: "memory");
    }
    __syncwarp();
#pragma unroll
    for (int s = 1; s < DCN_NF; s++) first_loads(s);
  }
  const int wg = wid >> 2;
  const int warp = wid & 3;
  const uint32_t rank = j & 1;
  const int short_t = (gridDim.x > 4 * kGroups && !helper) ? helped_round(grp) * kLayers : -8;
  const unsigned lend = helper ? ~0u : 1u;
  auto moves_up = [&](int t) { return (unsigned)(t + 1 - short_t) > lend; };

  if (wg == 2) {
    asm volatile("setmaxnreg.dec.sync.aligned.u32 40;");
    if (tid == 288) {
      if (sb & 1023) asm volatile("trap;");
      mbar_init(sb + BAR_BFULL, 1);
#pragma unroll
      for (int i = 0; i < NB; i++) mbar_init(sb + BAR_BEMPTY + i * 8, 2);
#pragma unroll
      for (int i = 0; i < 4; i++) mbar_init(sb + BAR_XREADY + i * 8, 1);
      mbar_init(sb + BAR_ORDER, 1);
    } else if (tid == 320) {
#pragma unroll
      for (int i = 0; i < 2 * NA; i++) { mbar_init(sb + BAR_AEMPTY + i * 8, 2); mbar_init(sb + BAR_STAGED + i * 8, 4); }
    } else if (tid == 352) {
#pragma unroll
      for (int i = 0; i < 8; i++) { mbar_init(sb + BAR_PFULL + i * 8, 1); mbar_init(sb + BAR_PFREE + i * 8, 1); }
      mbar_init(sb + BAR_BIAS, 32);
      asm volatile("st.shared.v4.f32 [%0], {%1, %1, %1, %1};" ::"r"(sb + OFF_INIT), "f"(kOffset) : "memory");
    }
    asm volatile("fence.mbarrier_init.release.cluster;" ::: "memory");
    __syncwarp();
    cluster_arrive_relaxed();
    if (tid == 288) PROF_ENDS(1000);
    if (warp == 0) {
      PROF_ST(6);
#pragma unroll 1
      for (int s = DCN_NF; s < 4; s++) first_loads(s);
      cluster_wait();
      PROF_ST(7);
      uint32_t par = 0;
      int l = 0;
      const int ntiles = helper ? kJobs : kTiles;
#pragma unroll 1
      for (int t = 0; t < ntiles; t++) {
        const int jo = (t == 0 && !helper) ? 0 : j;
        const int q_end = t == short_t ? 2 : 4;
#pragma unroll 1
        for (int q = (helper ? 2 : 0) + (t == 0); q < q_end; q++) {
          const int krow = l * kDim + kgroup_col(jo, q) * 256;
          const bool first = q == (helper ? 2 : 0);
          const bool up = q >= 2 && moves_up(t);
          const int shift = first ? (moves_up(t - 1) ? -1 : 0) : (up && q == 2 ? 1 : 0);
          const int paced = first ? (shift ? DRAIN + 1 : 0) : ((helper || (q == 1 && (t == short_t || t == 0))) ? 0 : NB);
          const uint32_t dst = sb + OFF_B + (up ? B_SLOT : 0);
          uint32_t full = sb + (first ? BAR_BFULL0 : BAR_BFULL);
#pragma unroll 1
          for (int i = 0; i < NB; i++) {
            if ((unsigned)(i + shift) < NB) mbar_spin(sb + BAR_BEMPTY + (i + shift) * 8, par);
            paced_load_3d_e(dst + i * B_SLOT, &mw, full, 0, krow + i * 32, j * 4, i < paced);
            full = sb + BAR_BFULL + 8 + i * 8;
            PROF_SKEW(t * 32 + q * 8 + i);
          }
          par ^= 1;
        }
        if (helper || ++l == kLayers) l = 0;
      }
    } else if (warp <= 2) {
      const int w = warp - 1;
      const uint32_t abase = sb + OFF_A + w * NA * A_SLOT;
      const uint32_t fullb = sb + BAR_AFULL + w * NA * 8;
      const uint32_t emptyb = sb + BAR_AEMPTY + w * 8;
      const uint32_t stagedb = sb + BAR_STAGED + w * NA * 8;
      const unsigned int base = __shfl_sync(0xffffffffu, *(volatile unsigned int*)(g_flags + (bid * 2 + w) * 32), 0);
      cluster_wait();
      uint32_t epar = 0;
      uint32_t spar = 0;
      auto refill = [&](const CUtensorMap* m, int col, int row) {
#pragma unroll 1
        for (int s = 0; s < 4; s++) {
          mbar_spin(emptyb + s * 16, epar);
          expect_load_2d_e<false>(abase + s * A_SLOT, m, fullb + s * 8, col + s * 64, row);
        }
        epar ^= 1;
      };
      auto store_refill = [&](int out_row, int col, int row, bool last_read) {
#pragma unroll 1
        for (int s = 0; s < 4; s++) {
          mbar_spin(stagedb + s * 8, spar);
          fence_async_smem();
          store_2d_e<true>(&mo64, abase + s * A_SLOT, j * 256 + s * 64, out_row);
          bulk_commit();
          bulk_wait<0>();
          __syncwarp();
          mbar_spin(emptyb + s * 16, epar);
          if (last_read) expect_load_2d_e<true>(abase + s * A_SLOT, &mx64, fullb + s * 8, col + s * 64, row);
          else expect_load_2d_e<false>(abase + s * A_SLOT, &mx64, fullb + s * 8, col + s * 64, row);
        }
        spar ^= 1;
        epar ^= 1;
      };
      auto store_tile = [&](auto stream, int out_row) {
#pragma unroll 1
        for (int c = 0; c < 4; c++) {
          mbar_spin(stagedb + c * 8, spar);
          PROF_EPI(c);
          fence_async_smem();
          arrive_e(fullb + c * 8);
          if (!decltype(stream)::value && w == 1) {
            bulk_commit();
            bulk_wait<0>();
          }
          store_2d_e<decltype(stream)::value>(&mo64, abase + c * A_SLOT, j * 256 + c * 64, out_row);
        }
        spar ^= 1;
        bulk_commit();
        bulk_wait<0>();
        __syncwarp();
      };
      auto refill_shared = [&](const CUtensorMap* m32, int col, int row) {
#pragma unroll 1
        for (int s = 0; s < 4; s++) {
          mbar_spin(emptyb + s * 16, epar);
          expect_load_2d_mc_e(abase + s * A_SLOT + rank * 4096, m32, fullb + s * 8, col + s * 64, row + rank * 32);
        }
        epar ^= 1;
      };
      if (helper) {
#pragma unroll 1
        for (int h = 1; h < 2 * kJobs; h++) refill_shared(&mx32, col0 + (h & 1) * 256, job_row(h >> 1) + w * 64);
      } else {
        const uint32_t xready_peer = map_cta(sb + BAR_XREADY + w * 8, rank ^ 1);
        const unsigned int* oflag = g_flags + ((grp * 4 + kgroup_col(j, 2)) * 2 + w) * 32;
        unsigned int* done_mine = g_flags + kFlagSet + (bid * 2 + w) * 32;
        const unsigned int* done_peer = g_flags + kFlagSet + ((bid ^ 2) * 2 + w) * 32;
        uint32_t nx = 0;
#pragma unroll 1
        for (int rd = 0; rd < kRounds; rd++) {
          const int xrow = (rd * kGroups + grp) * 128 + w * 64;
          if (rd == 0) {
            refill(&mx64, 256, xrow);
          } else {
            poll_flag(done_peer, base + nx);
            store_refill(xrow - kGroups * 128, (j ^ 1) * 256, xrow, rd * kLayers == short_t);
          }
          if (rd * kLayers != short_t) {
#pragma unroll 1
            for (int h = 0; h < 2; h++) refill_shared(&mx32, (kgroup_col(rd == 0 ? 0 : j, 2) + h) * 256, xrow);
          }
#pragma unroll 1
          for (int l = 1; l < kLayers; l++) {
            if (l > 1) poll_flag(done_peer, base + nx);
            store_tile(Flag<false>(), xrow);
            PROF_SVC((rd * kLayers + l - 1) * 2 + w);
            arrive_mapped_e(xready_peer);
            arrive_e(sb + BAR_PUB + w * 8);
            mbar_spin(sb + BAR_XREADY + w * 8, nx & 1);
            fence_async_global();
            refill(&mo64, (j ^ 1) * 256, xrow);
#pragma unroll 1
            for (int h = 0; h < 2; h++) {
              poll_flag(oflag + h * 64, base + nx + 1);
              fence_async_global();
              refill_shared(&mo32, (kgroup_col(j, 2) + h) * 256, xrow);
            }
            if (rank) {
#pragma unroll 1
              for (int s = 0; s < 4; s++) mbar_spin(fullb + s * 8, 1);
            }
            nx++;
            if ((tid & 31) == 0) st_relaxed(done_mine, base + (nx == kRounds * (kLayers - 1) ? kEpoch : nx));
            __syncwarp();
          }
          const int nrow = xrow + kGroups * 128;
          if (rd + 1 == kRounds) {
            poll_flag(done_peer, base + nx);
            store_tile(Flag<true>(), xrow);
            arrive_e(sb + BAR_PUB + w * 8);
          } else {
            refill(&mx64, j * 256, nrow);
          }
          PROF_SVC((rd * kLayers + kLayers - 1) * 2 + w);
        }
      }
    } else {
      const int lane = tid & 31;
      unsigned int* myflag = g_flags + bid * 2 * 32;
      if (lane == 0) { prefetch_map(&mx32); prefetch_map(&mo64); prefetch_map(&mo32); }
      const unsigned int base = *(volatile unsigned int*)myflag;
      auto publish = [&](uint32_t n, uint32_t value) {
#pragma unroll 1
        for (int w = 0; w < 2; w++) {
          mbar_wait(sb + BAR_PUB + w * 8, n & 1);
          asm volatile("fence.acq_rel.gpu;" ::: "memory");
          if (lane == 0) st_relaxed(myflag + w * 32, base + value);
          __syncwarp();
        }
      };
      if (helper) {
        mbar_arrive(sb + BAR_BIAS);
        cluster_wait();
#pragma unroll 1
        for (int n = 0; n < kJobs; n++) {
          if (n + 2 < kJobs) {
            const int row = job_row(n + 2);
#pragma unroll 1
            for (int i = 0; i < 8; i++) prefetch_2d_e(&mx64, col0 + rank * 256 + (i & 3) * 64, row + (i >> 2) * 64);
          }
          publish(n, n + 1);
        }
      } else {
        {
          float c[8];
#pragma unroll
          for (int i = 0; i < 8; i++) c[i] = 0.f;
#pragma unroll 1
          for (int l = 0; l < kLayers; l++) {
            const uint4 v = *reinterpret_cast<const uint4*>(bias + l * kDim + j * 256 + lane * 8);
            const uint32_t u[4] = {v.x, v.y, v.z, v.w};
#pragma unroll
            for (int i = 0; i < 4; i++) {
              c[2 * i] += __uint_as_float(u[i] << 16) + kTrunc;
              c[2 * i + 1] += __uint_as_float(u[i] & 0xffff0000u) + kTrunc;
              uint32_t pk;
              asm("cvt.rn.bf16x2.f32 %0, %1, %2;" : "=r"(pk) : "f"(c[2 * i + 1]), "f"(c[2 * i]));
              asm volatile("st.shared.u32 [%0], %1;" ::"r"(sb + OFF_BIAS + l * 512 + (lane >> 2) * 64 + i * 16 + (lane & 3) * 4),
                           "r"(pk) : "memory");
            }
          }
#pragma unroll
          for (int i = 0; i < 15; i++) {
            const uint32_t one = (lane >> 3) == (lane & 3) ? 0x3f80u << ((lane & 4) * 4) : 0u;
            asm volatile("st.shared.u32 [%0], %1;" ::"r"(sb + OFF_UNIT + i * 128 + lane * 4), "r"(i == 7 ? one : 0u) : "memory");
          }
          fence_async_smem();
          mbar_arrive(sb + BAR_BIAS);
        }
        const __nv_bfloat16* wslice = wptr + bid * 8192;
        cluster_wait();
        if (DCN_W1) __nanosleep(DCN_W1);
        prefetch_1d_e(wslice + kDim * kDim, 16384);
        uint32_t nx = 0;
#pragma unroll 1
        for (int rd = 0; rd < kRounds; rd++) {
#pragma unroll 1
          for (int l = 1; l < kLayers; l++) {
            publish(nx, nx + 1 == kRounds * (kLayers - 1) ? kEpoch : nx + 1);
            nx++;
            if (l < kLayers - 1) {
              if (rd == 0) prefetch_1d_e(wslice + (l + 1) * kDim * kDim, 16384);
            } else if (rd + 1 < kRounds) {
              const int nrow = ((rd + 1) * kGroups + grp) * 128;
#pragma unroll 1
              for (int i = 0; i < 8; i++) {
                prefetch_2d_e(&mx64, j * 256 + (i >> 1) * 64, nrow + (i & 1) * 64);
                __nanosleep(300);
              }
              if ((rd + 1) * kLayers == short_t) {
                poll_flag(g_flags + ((4 * kGroups + j) * 2 + 1) * 32, base + job_of_group(grp) + 1);
                fence_async_global();
                constexpr uint32_t order = 0x76325140;
#pragma unroll 1
                for (int i = NP; i < 8; i++)
                  prefetch_2d_e(&mp, j * 256 + ((order >> (i * 4)) & 3) * 64, nrow + ((order >> (i * 4)) & 4) * 16);
#pragma unroll 1
                for (int i = 0; i < 8; i++) {
                  if (i >= NP) mbar_wait(sb + BAR_PFREE + (i - NP) * 8, 0);
                  PROF(776 + i);
                  expect_load_2d_e<true>(sb + OFF_P + (i % NP) * A_SLOT, &mp, sb + BAR_PFULL + i * 8,
                                         j * 256 + ((order >> (i * 4)) & 3) * 64, nrow + ((order >> (i * 4)) & 4) * 16);
                }
              }
            }
          }
        }
#pragma unroll 1
        for (int w = 0; w < 2; w++) mbar_wait(sb + BAR_PUB + w * 8, nx & 1);
      }
    }
    if (warp == (helper ? 3 : 2) && (tid & 31) == 0) PROF_ENDS(1002);
    if (warp == 2) PROF_DUMP();
  } else {
    cluster_arrive_relaxed();
    asm volatile("setmaxnreg.inc.sync.aligned.u32 232;");
    PROF_ST(32);
    const int lane = tid & 31;
    const int wtid = tid & 127;
    const uint32_t abase = sb + OFF_A + wg * NA * A_SLOT;
    const uint32_t afull = sb + BAR_AFULL + wg * NA * 8;
    const uint32_t rel = map_cta(sb + (wtid == 64 ? BAR_BEMPTY : BAR_AEMPTY + wg * 8 - 8), wtid == 32 ? (rank ^ 1) : rank);
    const bool rel_b = wtid == 64;
    const bool rel_ab = (wtid & 31) == 0 && wtid < 96;
    const uint32_t frag0 = __shfl_sync(0xffffffffu, abase + ((wtid >> 5) * 16 + ((lane >> 3) & 1) * 8 + (lane & 7)) * 128 +
                                                        (((lane >> 4) ^ (lane & 7)) << 4), lane);
    const uint64_t adesc0 = desc(((abase & 0x3FFFF) >> 4) | DESC_A_LBO);
    const uint64_t bdesc0 = desc((((sb + OFF_B) & 0x3FFFF) >> 4) | DESC_B_LBO);

    const uint64_t zero = gridDim.y - 1;
    uint64_t adesc_q = adesc0 + zero, bdesc_q = bdesc0 + zero;

    float acc[128];
    uint32_t xr[64];
#pragma unroll
    for (int i = 0; i < 128; i++) acc[i] = kOffset;
#pragma unroll
    for (int i = 0; i < 64; i++) xr[i] = 0;
    int l = 0;
    bool hold = false;
    bool swap = false;
    bool brief = helper;
    int capture_q = helper ? -1 : j;

    auto release = [&](int i, bool with_a) {
      mbar_arrive_mapped_if(rel + i * 8, (i & 1) ? with_a : rel_b);
    };
    auto chunk_staged = [&](int c) {
      __syncwarp();
      arrive_e(sb + BAR_STAGED + (wg * NA + c) * 8);
    };
    auto capture_slot = [&](int p) {
#pragma unroll
      for (int g = 0; g < 4; g++) ldsm4(&xr[(p * 4 + g) * 4], (frag0 ^ (g * 32)) + p * A_SLOT);
    };
    auto swap_half = [&](int p, int half) {
#pragma unroll
      for (int g = half * 2; g < half * 2 + 2; g++) {
        const uint32_t addr = (frag0 ^ (g * 32)) + p * A_SLOT;
        uint32_t n[4];
        ldsm4(n, addr);
        stsm4(addr, &xr[(p * 4 + g) * 4]);
#pragma unroll
        for (int i = 0; i < 4; i++) xr[(p * 4 + g) * 4 + i] = n[i];
      }
      if (half) chunk_staged(p);
    };
    auto chunk_of = [&](int c) { return wg ? (0x7631 >> (c * 4)) & 7 : (0x5420 >> (c * 4)) & 7; };
    auto add_partial = [&](int c) __attribute__((always_inline)) {
      const int n = chunk_of(c);
      const int slot = wg ? (0x1001 >> (c * 4)) & 3 : (0x2120 >> (c * 4)) & 3;
      PROF(768 + wg * 16 + c * 2);
      mbar_spin(sb + BAR_PFULL + n * 8, 0);
      PROF(768 + wg * 16 + c * 2 + 1);
      wg_fence();
      wgmma_n256(acc, ((uint64_t)(128 >> 4) << 32) | ((128 >> 4) << 16) | (((sb + OFF_UNIT + (6 - 2 * c) * 128) & 0x3FFFF) >> 4),
                 ((uint64_t)(256 >> 4) << 32) | ((128 >> 4) << 16) | (((sb + OFF_P + slot * A_SLOT) & 0x3FFFF) >> 4));
    };
    auto issue = [&](int i, uint32_t par, int t, bool wait_b) __attribute__((always_inline)) {
      if (!(i & 1)) mbar_spin(afull + (i >> 1) * 8, par);
      if (wait_b) mbar_spin(sb + BAR_BFULL + i * 8, i == 0 ? (par ^ t ^ 1) & 1 : par);
      const uint64_t adesc = adesc_q + ((i >> 1) * (A_SLOT >> 4) + (i & 1) * 4);
      const uint64_t bdesc = bdesc_q + i * (B_SLOT >> 4);
      wg_fence();
      wgmma_n256(acc, adesc, bdesc);
      wgmma_n256(acc, adesc + 2, bdesc + 128);
      wg_commit();
      if (i == NB - 1) { adesc_q += zero; bdesc_q += zero; }
    };
    auto retire = [&](int i, bool with_a) {
      wg_wait<2>();
      release((i + 6) & 7, with_a);
    };
    auto k_loop = [&](auto first, int t) __attribute__((always_inline)) {
      constexpr bool FIRST = decltype(first)::value;
      const bool inject = FIRST && brief && !helper;
      const uint32_t up = moves_up(t) ? B_SLOT >> 4 : 0;
      auto extras = [&](int q, int i, bool swap_now) __attribute__((always_inline)) {
        if (!FIRST) return;
        if (swap_now) swap_half(((i + 5) >> 1) & 3, (i + 1) & 1);
        if ((i & 1) && q == capture_q) capture_slot(i >> 1);
      };
      auto free_partial = [&](int c) {
        if (FIRST) mbar_arrive_if(sb + BAR_PFREE + chunk_of(c) * 8, inject && rel_b);
      };
#pragma unroll
      for (int i = 1; i < 8; i++) {
        if (!(i & 1)) PROF(t * 32 + wg * 16 + 8 + (i >> 1));
        if ((i == 1 || i == 7) && inject) add_partial(i >> 2);
        issue(i, 0, t, true);
        if (i >= 2) retire(i, rel_ab);
        if (i == 3) free_partial(0);
        extras(0, i, i >= 3 && swap);
      }
      PROF(t * 32 + wg * 16 + 1);
      if (!FIRST || !brief) {
#pragma unroll 1
        for (int q = 1; q < 3; q++) {
#pragma unroll
          for (int i = 0; i < 8; i++) {
            issue(i, q & 1, t, true);
            if (i == 0) PROF(t * 32 + wg * 16 + 3 + q);
            retire(i, rel_ab);
            extras(q, i, i < 3 && swap);
          }
          if (FIRST) swap = false;
          if (q == 1) bdesc_q += up;
        }
      }
      const bool rel_last = rel_b | (hold & rel_ab);
      auto with_a = [&](int slot) { return slot == 7 ? rel_ab : rel_last; };
      constexpr int JOIN = DRAIN + 2;
      constexpr int INJ = JOIN < 3 ? 3 : JOIN;
#pragma unroll
      for (int i = 0; i < DRAIN; i++) {
        issue(i, 1, t, true);
        retire(i, with_a((i + 6) & 7));
        if (i == 1) free_partial(1);
        extras(3, i, i < 3 && swap);
      }
      if (wg == 1) {
        mbar_spin(sb + BAR_BFULL + DRAIN * 8, 1);
        wg_wait<1>();
        release((DRAIN + 6) & 7, with_a((DRAIN + 6) & 7));
        wg_wait<0>();
        release((DRAIN + 7) & 7, with_a((DRAIN + 7) & 7));
        if (DRAIN < 2) free_partial(1);
        PROF(t * 32 + wg * 16 + 12);
#pragma unroll
        for (int i = DRAIN; i < 3; i++) extras(-2, i, swap);
        mbar_spin(sb + BAR_ORDER, t & 1);
        PROF(t * 32 + wg * 16 + 6);
#pragma unroll
        for (int i = DRAIN; i < JOIN; i++) {
          issue(i, 1, t, i != DRAIN);
          extras(3, i, false);
        }
      } else {
        PROF(t * 32 + wg * 16 + 6);
#pragma unroll
        for (int i = DRAIN; i < JOIN; i++) {
          issue(i, 1, t, true);
          retire(i, with_a((i + 6) & 7));
          if (i == 1) free_partial(1);
          extras(3, i, i < 3 && swap);
        }
      }
#pragma unroll
      for (int i = JOIN; i < 8; i++) {
        if ((i == INJ || i == 7) && inject) add_partial(i == INJ ? 2 : 3);
        issue(i, 1, t, true);
        if (i == 7) mbar_arrive_if(sb + BAR_ORDER, rel_b & (wg == 0));
        retire(i, rel_last);
        if (i == INJ + 2) free_partial(2);
        extras(3, i, false);
      }
      bdesc_q -= up;
    };

    auto epilogue = [&](auto kind, int t, bool more) __attribute__((always_inline)) {
      constexpr int KIND = decltype(kind)::value;
      constexpr int PRE = KIND == 0 ? BPRE : (KIND == 1 ? HPRE : 0);
      if (KIND != 1 && t == 0) mbar_spin(sb + BAR_BIAS, 0);
      const uint32_t bl = sb + OFF_BIAS + (KIND == 1 ? kLayers - 1 : l) * 512 + ((frag0 >> 3) & 0x30);
      uint32_t bq[8][4];
      auto load_bias = [&](int U) {
        asm volatile("ld.shared.v4.u32 {%0, %1, %2, %3}, [%4];"
                     : "=r"(bq[U][0]), "=r"(bq[U][1]), "=r"(bq[U][2]), "=r"(bq[U][3]) : "r"(bl + U * 64));
      };
#pragma unroll
      for (int U = 0; U < PRE; U++) load_bias(U);
      wg_wait<1>();
      release(6, false);
      if (more) mbar_spin(sb + BAR_BFULL0, (t + 1) & 1);
      wg_wait<0>();
#pragma unroll
      for (int i = 0; i < 128; i++) asm volatile("" : "+f"(acc[i]) :: "memory");
      release(7, KIND == 0 ? rel_b : (KIND == 1 ? rel_ab : rel_b | (more & rel_ab)));
      PROF(t * 32 + wg * 16 + 2);
      if (t == 0) PROF_ST(30 + wg);

      auto pack = [&](int i, float off) {
        uint32_t v;
        asm("cvt.rn.bf16x2.f32 %0, %1, %2;" : "=r"(v) : "f"(acc[i * 2 + 1] - off), "f"(acc[i * 2] - off));
        return v;
      };
      auto cross = [&](int T, int i, float off) {
        uint32_t s2 = pack(T * 4 + i, off), o;
        asm("add.rn.bf16x2 %0, %1, %2;" : "=r"(s2) : "r"(s2), "r"(bq[T >> 1][(T & 1) * 2 + (i >> 1)]));
        asm("fma.rn.bf16x2 %0, %1, %2, %1;" : "=r"(o) : "r"(xr[T * 4 + i]), "r"(s2));
        return o;
      };
      auto reset = [&](int T) {
#pragma unroll
        for (int i = T * 8; i < T * 8 + 8; i += 4)
          asm volatile("ld.volatile.shared.v4.f32 {%0, %1, %2, %3}, [%4];"
                       : "+f"(acc[i]), "+f"(acc[i + 1]), "+f"(acc[i + 2]), "+f"(acc[i + 3]) : "r"(sb + OFF_INIT));
      };
      auto offset_for = [&](int T) { return T >= LAG ? acc[(T - LAG) * 8 + 7] : kOffset; };
      if (KIND == 2) {
        uint32_t id;
        asm volatile("mov.u32 %0, %%tid.x;" : "=r"(id));
        __nv_bfloat16* dst = optr + (size_t)(job_row(t) + wg * 64) * kDim + j * 256 + (id & 127) * 2;
        uint64_t pol;
        asm volatile("createpolicy.fractional.L2::evict_first.b64 %0, 1.0;" : "=l"(pol));
#pragma unroll
        for (int T = 0; T < 16; T++) {
#pragma unroll
          for (int i = 0; i < 4; i++)
            asm volatile("st.global.L2::cache_hint.b32 [%0], %1, %2;"
                         ::"l"(dst + (T * 4 + (i ^ 1)) * kDim), "r"(pack(T * 4 + i, offset_for(T))), "l"(pol) : "memory");
          reset(T);
        }
        asm volatile("bar.sync %0, 128;" ::"r"(wg + 1) : "memory");
        mbar_arrive_if(sb + BAR_PUB + wg * 8, rel_b);
      } else if (KIND == 1) {
#pragma unroll
        for (int T = 0; T < 16; T++) {
#pragma unroll
          for (int i = 0; i < 4; i++) xr[T * 4 + i] = cross(T, i, offset_for(T));
          if ((T & 1) && (T >> 1) + PRE < 8) load_bias((T >> 1) + PRE);
          reset(T);
        }
      } else {
#pragma unroll
        for (int T = 0; T < 16; T++) {
          uint32_t o[4];
#pragma unroll
          for (int i = 0; i < 4; i++) o[i] = cross(T, i, kOffset);
          stsm4((frag0 ^ ((T & 3) * 32)) + (T >> 2) * A_SLOT, o);
          if ((T & 3) == 3) chunk_staged(T >> 2);
          if ((T & 1) && (T >> 1) + PRE < 8) load_bias((T >> 1) + PRE);
        }
        PROF(t * 32 + wg * 16 + 7);
      }
      PROF(t * 32 + wg * 16 + 3);
    };

    PROF_ST(8);
    cluster_wait();
    PROF_ST(9);
    mbar_spin(sb + BAR_BFULL0, 0);
    PROF_ST(10);
    int t = 0;
#pragma unroll 1
    while (true) {
      if (t > 0) {
        if (helper) {
          epilogue(Int<2>(), t - 1, t < kJobs);
          if (t == kJobs) break;
        } else {
          epilogue(Int<1>(), t - 1, true);
        }
      }
      issue(0, 0, 0, false);
      if (t == 0) PROF_ST(11);
      l = 0;
      swap = t > 0 && !helper;
      brief = helper || t == short_t;
      hold = helper && t + 1 < kJobs;
      capture_q = (t > 0 || helper) ? -1 : j;
      PROF(t * 32 + wg * 16 + 0);
      k_loop(Flag<true>(), t);
      t++;
      if (helper) continue;
#pragma unroll 1
      do {
        epilogue(Int<0>(), t - 1, t < kTiles);
        if (t == kTiles) asm volatile("exit;");
        issue(0, 0, 0, false);
        l++;
        hold = l == kLayers - 1 && t + 1 < kTiles;
        PROF(t * 32 + wg * 16 + 0);
        k_loop(Flag<false>(), t);
        t++;
      } while (!hold);
    }
  }
}

__global__ void __launch_bounds__(256) dcn_fallback(const __nv_bfloat16* __restrict__ x0, const __nv_bfloat16* __restrict__ w,
                                                    const __nv_bfloat16* __restrict__ b, __nv_bfloat16* __restrict__ out) {
  __shared__ float xs[8][kDim];
  const size_t r0 = (size_t)blockIdx.x * 8;
  for (int i = threadIdx.x; i < 8 * kDim; i += 256) xs[i / kDim][i % kDim] = __bfloat162float(x0[r0 * kDim + i]);
  __syncthreads();
  for (int l = 0; l < kLayers; l++) {
    float a[4][8] = {};
    for (int k = 0; k < kDim; k++) {
#pragma unroll
      for (int c = 0; c < 4; c++) {
        const float wv = __bfloat162float(w[((size_t)l * kDim + k) * kDim + c * 256 + threadIdx.x]);
#pragma unroll
        for (int r = 0; r < 8; r++) a[c][r] += xs[r][k] * wv;
      }
    }
    __syncthreads();
#pragma unroll
    for (int c = 0; c < 4; c++) {
      const int n = c * 256 + threadIdx.x;
#pragma unroll
      for (int r = 0; r < 8; r++) {
        const float v = __bfloat162float(x0[(r0 + r) * kDim + n]) * (a[c][r] + __bfloat162float(b[l * kDim + n])) + xs[r][n];
        xs[r][n] = __bfloat162float(__float2bfloat16(v));
      }
    }
    __syncthreads();
  }
  for (int i = threadIdx.x; i < 8 * kDim; i += 256) out[r0 * kDim + i] = __float2bfloat16(xs[i / kDim][i % kDim]);
}

typedef CUresult (*EncodeFn)(CUtensorMap*, CUtensorMapDataType, cuuint32_t, void*, const cuuint64_t*, const cuuint64_t*,
                             const cuuint32_t*, const cuuint32_t*, CUtensorMapInterleave, CUtensorMapSwizzle,
                             CUtensorMapL2promotion, CUtensorMapFloatOOBfill);

static void make_map_2d(EncodeFn enc, CUtensorMap* m, void* ptr, uint64_t rows, uint32_t box_rows,
                        CUtensorMapSwizzle swizzle = CU_TENSOR_MAP_SWIZZLE_128B) {
  cuuint64_t dims[2] = {(cuuint64_t)kDim, rows};
  cuuint64_t strides[1] = {kDim * 2};
  cuuint32_t box[2] = {64, box_rows};
  cuuint32_t es[2] = {1, 1};
  enc(m, CU_TENSOR_MAP_DATA_TYPE_BFLOAT16, 2, ptr, dims, strides, box, es, CU_TENSOR_MAP_INTERLEAVE_NONE,
      swizzle, CU_TENSOR_MAP_L2_PROMOTION_L2_128B, CU_TENSOR_MAP_FLOAT_OOB_FILL_NONE);
}

}

extern "C" void kernel_launch(void* const* d_in, const int* in_sizes, int n_in, void* d_out, int out_size) {
  using namespace dcn;
  (void)in_sizes; (void)n_in; (void)out_size;
  void* fn = nullptr;
  cudaDriverEntryPointQueryResult qr;
  cudaGetDriverEntryPoint("cuTensorMapEncodeTiled", &fn, cudaEnableDefault, &qr);
  EncodeFn enc = (EncodeFn)fn;
  CUtensorMap mx64, mx32, mo64, mo32, mw, mp;
  make_map_2d(enc, &mx64, d_in[0], kRows, 64);
  make_map_2d(enc, &mx32, d_in[0], kRows, 32);
  make_map_2d(enc, &mo64, d_out, kRows, 64);
  make_map_2d(enc, &mo32, d_out, kRows, 32);
  make_map_2d(enc, &mp, d_out, kRows, 64, CU_TENSOR_MAP_SWIZZLE_NONE);
  {
    cuuint64_t dims[3] = {64, (cuuint64_t)kLayers * kDim, kDim / 64};
    cuuint64_t strides[2] = {kDim * 2, 128};
    cuuint32_t box[3] = {64, 32, 4};
    cuuint32_t es[3] = {1, 1, 1};
    enc(&mw, CU_TENSOR_MAP_DATA_TYPE_BFLOAT16, 3, d_in[1], dims, strides, box, es, CU_TENSOR_MAP_INTERLEAVE_NONE,
        CU_TENSOR_MAP_SWIZZLE_128B, CU_TENSOR_MAP_L2_PROMOTION_L2_128B, CU_TENSOR_MAP_FLOAT_OOB_FILL_NONE);
  }
  const __nv_bfloat16* x0 = (const __nv_bfloat16*)d_in[0];
  const __nv_bfloat16* w = (const __nv_bfloat16*)d_in[1];
  const __nv_bfloat16* b = (const __nv_bfloat16*)d_in[2];
  __nv_bfloat16* out = (__nv_bfloat16*)d_out;
  constexpr int smem = SMEM_BYTES + PROF_SMEM;
  cudaFuncSetAttribute(dcn_kernel, cudaFuncAttributeMaxDynamicSharedMemorySize, smem);

  cudaLaunchConfig_t cfg = {};
  cfg.gridDim = dim3(4 * kGroups + 4);
  cfg.blockDim = dim3(384);
  cfg.dynamicSmemBytes = smem;
  cudaLaunchAttribute attr;
  attr.id = cudaLaunchAttributeClusterDimension;
  attr.val.clusterDim.x = 2;
  attr.val.clusterDim.y = 1;
  attr.val.clusterDim.z = 1;
  cfg.attrs = &attr;
  cfg.numAttrs = 1;
  int clusters = 0;
  cudaOccupancyMaxActiveClusters(&clusters, dcn_kernel, &cfg);
  if (clusters >= 2 * kGroups) {
    const int grid = 4 * kGroups + (clusters >= 2 * kGroups + 2 ? 4 : 0);
    dcn_kernel<<<grid, 384, smem>>>(x0, w, b, out, mx64, mx32, mo64, mo32, mw, mp);
  } else {
    dcn_fallback<<<kRows / 8, 256>>>(x0, w, b, out);
  }
}
```

```cpp
#include <cuda_runtime.h>
#include <cuda.h>
#include <cuda_bf16.h>
#include <stdint.h>

namespace dcn {

__device__ __forceinline__ void wgmma_n256(float (&d)[128], uint64_t da, uint64_t db) {
  asm volatile("wgmma.mma_async.sync.aligned.m64n256k16.f32.bf16.bf16 "
    "{%0, %1, %2, %3, %4, %5, %6, %7, %8, %9, %10, %11, %12, %13, %14, %15, %16, %17, %18, %19, %20, %21, %22, %23, %24, %25, %26, %27, %28, %29, %30, %31, %32, %33, %34, %35, %36, %37, %38, %39, %40, %41, %42, %43, %44, %45, %46, %47, %48, %49, %50, %51, %52, %53, %54, %55, %56, %57, %58, %59, %60, %61, %62, %63, %64, %65, %66, %67, %68, %69, %70, %71, %72, %73, %74, %75, %76, %77, %78, %79, %80, %81, %82, %83, %84, %85, %86, %87, %88, %89, %90, %91, %92, %93, %94, %95, %96, %97, %98, %99, %100, %101, %102, %103, %104, %105, %106, %107, %108, %109, %110, %111, %112, %113, %114, %115, %116, %117, %118, %119, %120, %121, %122, %123, %124, %125, %126, %127}, "
    "%128, %129, 1, 1, 1, 0, 1;\n"
    : "+f"(d[0]), "+f"(d[1]), "+f"(d[2]), "+f"(d[3]), "+f"(d[4]), "+f"(d[5]), "+f"(d[6]), "+f"(d[7]), "+f"(d[8]), "+f"(d[9]), "+f"(d[10]), "+f"(d[11]), "+f"(d[12]), "+f"(d[13]), "+f"(d[14]), "+f"(d[15]), "+f"(d[16]), "+f"(d[17]), "+f"(d[18]), "+f"(d[19]), "+f"(d[20]), "+f"(d[21]), "+f"(d[22]), "+f"(d[23]), "+f"(d[24]), "+f"(d[25]), "+f"(d[26]), "+f"(d[27]), "+f"(d[28]), "+f"(d[29]), "+f"(d[30]), "+f"(d[31]), "+f"(d[32]), "+f"(d[33]), "+f"(d[34]), "+f"(d[35]), "+f"(d[36]), "+f"(d[37]), "+f"(d[38]), "+f"(d[39]), "+f"(d[40]), "+f"(d[41]), "+f"(d[42]), "+f"(d[43]), "+f"(d[44]), "+f"(d[45]), "+f"(d[46]), "+f"(d[47]), "+f"(d[48]), "+f"(d[49]), "+f"(d[50]), "+f"(d[51]), "+f"(d[52]), "+f"(d[53]), "+f"(d[54]), "+f"(d[55]), "+f"(d[56]), "+f"(d[57]), "+f"(d[58]), "+f"(d[59]), "+f"(d[60]), "+f"(d[61]), "+f"(d[62]), "+f"(d[63]), "+f"(d[64]), "+f"(d[65]), "+f"(d[66]), "+f"(d[67]), "+f"(d[68]), "+f"(d[69]), "+f"(d[70]), "+f"(d[71]), "+f"(d[72]), "+f"(d[73]), "+f"(d[74]), "+f"(d[75]), "+f"(d[76]), "+f"(d[77]), "+f"(d[78]), "+f"(d[79]), "+f"(d[80]), "+f"(d[81]), "+f"(d[82]), "+f"(d[83]), "+f"(d[84]), "+f"(d[85]), "+f"(d[86]), "+f"(d[87]), "+f"(d[88]), "+f"(d[89]), "+f"(d[90]), "+f"(d[91]), "+f"(d[92]), "+f"(d[93]), "+f"(d[94]), "+f"(d[95]), "+f"(d[96]), "+f"(d[97]), "+f"(d[98]), "+f"(d[99]), "+f"(d[100]), "+f"(d[101]), "+f"(d[102]), "+f"(d[103]), "+f"(d[104]), "+f"(d[105]), "+f"(d[106]), "+f"(d[107]), "+f"(d[108]), "+f"(d[109]), "+f"(d[110]), "+f"(d[111]), "+f"(d[112]), "+f"(d[113]), "+f"(d[114]), "+f"(d[115]), "+f"(d[116]), "+f"(d[117]), "+f"(d[118]), "+f"(d[119]), "+f"(d[120]), "+f"(d[121]), "+f"(d[122]), "+f"(d[123]), "+f"(d[124]), "+f"(d[125]), "+f"(d[126]), "+f"(d[127])
    : "l"(da), "l"(db));
}

constexpr int kDim = 1024;
constexpr int kRows = 16384;
constexpr int kLayers = 6;
constexpr int kGroups = 32;
constexpr int kRounds = kRows / 128 / kGroups;
constexpr int kTiles = kRounds * kLayers;

constexpr int kJobs = kGroups;
constexpr int kEpoch = 32;
constexpr int NA = 4;
constexpr int NB = 8;
constexpr float kOffset = 85.333336f;
constexpr float kTrunc = 64 * 0.375f / 131072;
constexpr int DRAIN = 1;
constexpr int LAG = 3;
constexpr int BPRE = 5;
constexpr int HPRE = 6;
constexpr int NF = 2;
constexpr int A_SLOT = 8192;
constexpr int B_SLOT = 16384;
constexpr int OFF_B = 0;
constexpr int NP = 3;
constexpr int OFF_P = OFF_B + NB * B_SLOT;
constexpr int OFF_A = OFF_P + NP * A_SLOT;
constexpr int OFF_UNIT = OFF_A + 2 * NA * A_SLOT;
constexpr int OFF_BIAS = OFF_UNIT + 2048;
constexpr int OFF_INIT = OFF_BIAS + kLayers * 256 * 2;
constexpr int OFF_BAR = OFF_INIT + 16;
constexpr int BAR_BFULL = OFF_BAR;
constexpr int BAR_BFULL0 = BAR_BFULL + NB * 8;
constexpr int BAR_BEMPTY = BAR_BFULL0 + NB * 8;
constexpr int BAR_AFULL = BAR_BEMPTY + NB * 8;
constexpr int BAR_AEMPTY = BAR_AFULL + 2 * NA * 8;
constexpr int BAR_XREADY = BAR_AEMPTY + 2 * NA * 8;
constexpr int BAR_PUB = BAR_XREADY + 16;
constexpr int BAR_PFULL = BAR_PUB + 16;
constexpr int BAR_PFREE = BAR_PFULL + 8 * 8;
constexpr int BAR_STAGED = BAR_PFREE + 8 * 8;
constexpr int BAR_ORDER = BAR_STAGED + 2 * NA * 8;
constexpr int BAR_BIAS = BAR_ORDER + 8;
constexpr int SMEM_BYTES = BAR_BIAS + 8;
static_assert(SMEM_BYTES <= 232448, "shared memory budget");

constexpr int kFlagSet = 4 * (kGroups + 1) * 2 * 32;
__device__ unsigned int g_flags[2 * kFlagSet];

__device__ __forceinline__ uint32_t smem_u32(const void* p) { return (uint32_t)__cvta_generic_to_shared(p); }
__device__ __forceinline__ void mbar_init(uint32_t bar, int cnt) {
  asm volatile("mbarrier.init.shared::cta.b64 [%0], %1;" ::"r"(bar), "r"(cnt) : "memory");
}
__device__ __forceinline__ void mbar_arrive(uint32_t bar) {
  asm volatile("mbarrier.arrive.shared::cta.b64 _, [%0];" ::"r"(bar) : "memory");
}
__device__ __forceinline__ uint32_t map_cta(uint32_t addr, uint32_t cta) {
  uint32_t r;
  asm volatile("mapa.shared::cluster.u32 %0, %1, %2;" : "=r"(r) : "r"(addr), "r"(cta));
  return r;
}
__device__ __forceinline__ void mbar_arrive_mapped_if(uint32_t cluster_addr, bool pred) {
  asm volatile("{\n.reg .pred p;\nsetp.ne.u32 p, %1, 0;\n@p mbarrier.arrive.shared::cluster.b64 _, [%0];\n}"
               ::"r"(cluster_addr), "r"((uint32_t)pred) : "memory");
}
__device__ __forceinline__ void mbar_arrive_if(uint32_t bar, bool pred) {
  asm volatile("{\n.reg .pred p;\nsetp.ne.u32 p, %1, 0;\n@p mbarrier.arrive.shared::cta.b64 _, [%0];\n}"
               ::"r"(bar), "r"((uint32_t)pred) : "memory");
}
__device__ __forceinline__ void mbar_wait(uint32_t bar, uint32_t parity) {
  asm volatile(
      "{\n.reg .pred p;\n.reg .u32 c;\n"
      "mbarrier.try_wait.parity.shared::cta.b64 p, [%0], %1;\n"
      "@p bra DONE;\n"
      "mov.u32 c, 0;\n"
      "LOOP:\n"
      "mbarrier.try_wait.parity.shared::cta.b64 p, [%0], %1;\n"
      "@p bra DONE;\n"
      "add.u32 c, c, 1;\n"
      "setp.lt.u32 p, c, 1048576;\n"
      "@p bra LOOP;\n"
      "trap;\n"
      "DONE:\n}"
      ::"r"(bar), "r"(parity) : "memory");
}
__device__ __forceinline__ void mbar_spin(uint32_t bar, uint32_t parity) {
  asm volatile(
      "{\n.reg .pred p;\n"
      "LOOP:\n"
      "mbarrier.try_wait.parity.shared::cta.b64 p, [%0], %1;\n"
      "@!p bra LOOP;\n}"
      ::"r"(bar), "r"(parity) : "memory");
}
#define ELECT_BEGIN "{\n.reg .pred e;\nelect.sync _|e, 0xffffffff;\n"
template <bool STREAM> __device__ __forceinline__ void expect_load_2d_e(uint32_t dst, const CUtensorMap* m, uint32_t bar, int c0, int c1) {
  if (STREAM) {
    asm volatile(ELECT_BEGIN ".reg .b64 pol;\ncreatepolicy.fractional.L2::evict_first.b64 pol, 1.0;\n"
                 "@e mbarrier.arrive.expect_tx.shared::cta.b64 _, [%2], 8192;\n"
                 "@e cp.async.bulk.tensor.2d.shared::cluster.global.mbarrier::complete_tx::bytes.L2::cache_hint [%0], [%1, {%3, %4}], [%2], pol;\n}"
                 ::"r"(dst), "l"(m), "r"(bar), "r"(c0), "r"(c1) : "memory");
  } else {
    asm volatile(ELECT_BEGIN
                 "@e mbarrier.arrive.expect_tx.shared::cta.b64 _, [%2], 8192;\n"
                 "@e cp.async.bulk.tensor.2d.shared::cluster.global.mbarrier::complete_tx::bytes [%0], [%1, {%3, %4}], [%2];\n}"
                 ::"r"(dst), "l"(m), "r"(bar), "r"(c0), "r"(c1) : "memory");
  }
}
__device__ __forceinline__ void expect_load_2d_mc_e(uint32_t dst, const CUtensorMap* m, uint32_t bar, int c0, int c1) {
  asm volatile(ELECT_BEGIN ".reg .b64 pol;\ncreatepolicy.fractional.L2::evict_first.b64 pol, 1.0;\n"
               "@e mbarrier.arrive.expect_tx.shared::cta.b64 _, [%2], 8192;\n"
               "@e cp.async.bulk.tensor.2d.shared::cluster.global.mbarrier::complete_tx::bytes.multicast::cluster.L2::cache_hint [%0], [%1, {%3, %4}], [%2], %5, pol;\n}"
               ::"r"(dst), "l"(m), "r"(bar), "r"(c0), "r"(c1), "h"((uint16_t)3) : "memory");
}
__device__ __forceinline__ void expect_load_3d_e(uint32_t dst, const CUtensorMap* m, uint32_t bar, int c0, int c1, int c2) {
  asm volatile(ELECT_BEGIN
               "@e mbarrier.arrive.expect_tx.shared::cta.b64 _, [%2], 16384;\n"
               "@e cp.async.bulk.tensor.3d.shared::cluster.global.mbarrier::complete_tx::bytes [%0], [%1, {%3, %4, %5}], [%2];\n}"
               ::"r"(dst), "l"(m), "r"(bar), "r"(c0), "r"(c1), "r"(c2) : "memory");
}
template <bool STREAM> __device__ __forceinline__ void store_2d_e(const CUtensorMap* m, uint32_t src, int c0, int c1) {
  if (STREAM) {
    asm volatile(ELECT_BEGIN ".reg .b64 pol;\ncreatepolicy.fractional.L2::evict_first.b64 pol, 1.0;\n"
                 "@e cp.async.bulk.tensor.2d.global.shared::cta.bulk_group.L2::cache_hint [%0, {%2, %3}], [%1], pol;\n}"
                 ::"l"(m), "r"(src), "r"(c0), "r"(c1) : "memory");
  } else {
    asm volatile(ELECT_BEGIN
                 "@e cp.async.bulk.tensor.2d.global.shared::cta.bulk_group [%0, {%2, %3}], [%1];\n}"
                 ::"l"(m), "r"(src), "r"(c0), "r"(c1) : "memory");
  }
}
__device__ __forceinline__ void prefetch_2d_e(const CUtensorMap* m, int c0, int c1) {
  asm volatile(ELECT_BEGIN
               "@e cp.async.bulk.prefetch.tensor.2d.L2.global [%0, {%1, %2}];\n}"
               ::"l"(m), "r"(c0), "r"(c1) : "memory");
}
__device__ __forceinline__ void prefetch_1d_e(const void* ptr, uint32_t bytes) {
  asm volatile(ELECT_BEGIN
               "@e cp.async.bulk.prefetch.L2.global [%0], %1;\n}"
               ::"l"(ptr), "r"(bytes) : "memory");
}
__device__ __forceinline__ void paced_load_3d_e(uint32_t dst, const CUtensorMap* m, uint32_t bar, int c0, int c1, int c2, bool pace) {
  asm volatile(ELECT_BEGIN ".reg .pred p;\nsetp.ne.u32 p, %6, 0;\n"
               "@e mbarrier.arrive.expect_tx.shared::cta.b64 _, [%2], 16384;\n"
               "@p nanosleep.u32 128;\n"
               "@e cp.async.bulk.tensor.3d.shared::cluster.global.mbarrier::complete_tx::bytes [%0], [%1, {%3, %4, %5}], [%2];\n}"
               ::"r"(dst), "l"(m), "r"(bar), "r"(c0), "r"(c1), "r"(c2), "r"((uint32_t)pace) : "memory");
}
__device__ __forceinline__ void arrive_mapped_e(uint32_t cluster_addr) {
  asm volatile(ELECT_BEGIN "@e mbarrier.arrive.shared::cluster.b64 _, [%0];\n}" ::"r"(cluster_addr) : "memory");
}
__device__ __forceinline__ void arrive_e(uint32_t bar) {
  asm volatile(ELECT_BEGIN "@e mbarrier.arrive.shared::cta.b64 _, [%0];\n}" ::"r"(bar) : "memory");
}
__device__ __forceinline__ void bulk_commit() { asm volatile("cp.async.bulk.commit_group;" ::: "memory"); }
template <int N> __device__ __forceinline__ void bulk_wait() { asm volatile("cp.async.bulk.wait_group %0;" ::"n"(N) : "memory"); }
__device__ __forceinline__ void wg_fence() { asm volatile("wgmma.fence.sync.aligned;" ::: "memory"); }
__device__ __forceinline__ void wg_commit() { asm volatile("wgmma.commit_group.sync.aligned;" ::: "memory"); }
template <int N> __device__ __forceinline__ void wg_wait() { asm volatile("wgmma.wait_group.sync.aligned %0;" ::"n"(N) : "memory"); }
__device__ __forceinline__ void fence_async_global() { asm volatile("fence.proxy.async.global;" ::: "memory"); }
__device__ __forceinline__ void st_relaxed(unsigned int* p, unsigned int v) {
  asm volatile("st.relaxed.gpu.global.u32 [%0], %1;" ::"l"(p), "r"(v) : "memory");
}
__device__ __forceinline__ void ldsm4(uint32_t* r, uint32_t addr) {
  asm volatile("ldmatrix.sync.aligned.m8n8.x4.shared.b16 {%0, %1, %2, %3}, [%4];"
               : "=r"(r[0]), "=r"(r[1]), "=r"(r[2]), "=r"(r[3]) : "r"(addr) : "memory");
}
__device__ __forceinline__ void stsm4(uint32_t addr, const uint32_t* r) {
  asm volatile("stmatrix.sync.aligned.m8n8.x4.shared.b16 [%0], {%1, %2, %3, %4};"
               ::"r"(addr), "r"(r[0]), "r"(r[1]), "r"(r[2]), "r"(r[3]) : "memory");
}
template <bool V> struct Flag { static constexpr bool value = V; };
template <int V> struct Int { static constexpr int value = V; };
__device__ __forceinline__ void fence_async_smem() { asm volatile("fence.proxy.async.shared::cta;" ::: "memory"); }
__device__ __forceinline__ void cluster_arrive_relaxed() { asm volatile("barrier.cluster.arrive.relaxed.aligned;" ::: "memory"); }
__device__ __forceinline__ void cluster_wait() { asm volatile("barrier.cluster.wait.acquire.aligned;" ::: "memory"); }
__device__ __forceinline__ void prefetch_map(const CUtensorMap* m) {
  asm volatile("prefetch.tensormap [%0];" ::"l"(m) : "memory");
}
__device__ __forceinline__ void prefetch_map_e(const CUtensorMap* m) {
  asm volatile(ELECT_BEGIN "@e prefetch.tensormap [%0];\n}" ::"l"(m) : "memory");
}
__device__ __forceinline__ void poll_flag(const unsigned int* ptr, unsigned int target) {
  asm volatile(
      "{\n.reg .pred p;\n.reg .u32 c;\n.reg .s32 v;\n"
      "mov.u32 c, 0;\n"
      "LOOP:\n"
      "ld.acquire.gpu.global.s32 v, [%0];\n"
      "sub.s32 v, v, %1;\n"
      "setp.ge.s32 p, v, 0;\n"
      "@p bra DONE;\n"
      "add.u32 c, c, 1;\n"
      "setp.lt.u32 p, c, 1048576;\n"
      "@p bra LOOP;\n"
      "trap;\n"
      "DONE:\n}"
      ::"l"(ptr), "r"(target) : "memory");
}

constexpr uint32_t DESC_HI = (1024u >> 4) | (1u << 30);
__device__ __forceinline__ uint64_t desc(uint32_t lo) { return ((uint64_t)DESC_HI << 32) | lo; }
constexpr uint32_t DESC_A_LBO = 1u << 16;
constexpr uint32_t DESC_B_LBO = (4096u >> 4) << 16;

__device__ __forceinline__ int kgroup_col(int j, int q) {
  return q == 0 ? j : (q == 1 ? (j ^ 1) : (((j ^ 2) & ~1) + (q - 2)));
}

__device__ __forceinline__ int role_of_cluster(int c) {
  const int a = c - 4;
  const int b = c - 36, r = (b * 37) >> 8;
  const int first = (a & ~7) + (a & 3) * 2 + ((a >> 2) & 1);
  const int second = 32 + r * 8 + ((0x7531640 >> (((b - r * 7) * 4) & 31)) & 7);
  return c >= 2 * kGroups ? c : (c >= 36 ? second : (c >= 4 ? first : 34 + c * 8));
}
__device__ __forceinline__ int helped_round(int grp) { return (grp & 2) ? (grp & 3) - 1 : 3; }
__device__ __forceinline__ int job_of_group(int grp) {
  return (grp & 2) ? (grp & 1) * 8 + (grp >> 2) : 16 + (grp >> 2) * 2 + (grp & 1);
}
__device__ __forceinline__ int job_row(int n) {
  const int grp = n < 16 ? (n & 7) * 4 + 2 + (n >> 3) : ((n - 16) >> 1) * 4 + (n & 1);
  return (helped_round(grp) * kGroups + grp) * 128;
}

#define PROF_ENDS(idx) do {} while (0)
#define PROF_SVC(idx) do {} while (0)
#define PROF_ST(idx) do {} while (0)
#define PROF_EPI(c) do {} while (0)
#define PROF_SKEW(idx) do {} while (0)
#define PROF(idx) do {} while (0)
#define PROF_DUMP() do {} while (0)
constexpr int PROF_SMEM = 0;

__global__ void __cluster_dims__(2, 1, 1) __launch_bounds__(384, 1)
dcn_kernel(const __nv_bfloat16* __restrict__ xptr, const __nv_bfloat16* __restrict__ wptr,
           const __nv_bfloat16* __restrict__ bias, __nv_bfloat16* optr,
           const __grid_constant__ CUtensorMap mx64, const __grid_constant__ CUtensorMap mx32,
           const __grid_constant__ CUtensorMap mo64, const __grid_constant__ CUtensorMap mo32,
           const __grid_constant__ CUtensorMap mw, const __grid_constant__ CUtensorMap mp) {
  extern __shared__ __align__(1024) uint8_t smem_raw[];
  const uint32_t sb = smem_u32(smem_raw);
  const int tid = threadIdx.x;
  if ((tid >> 5) == 8) PROF_ST(0);
  const int wid = __shfl_sync(0xffffffffu, tid >> 5, 0);
  if (wid == 0) {
    asm volatile("prefetch.global.L2 [%0];" ::"l"(wptr + ((blockIdx.x & 31) * 32 + tid) * 64));
    asm volatile("prefetch.global.L2 [%0];" ::"l"(xptr + ((blockIdx.x & 127) * 32 + tid) * kDim));
    prefetch_map_e(&mw);
    prefetch_map_e(&mx64);
    PROF_ST(29);
  }
  const int bid = role_of_cluster(blockIdx.x >> 1) * 2 + (blockIdx.x & 1);
  const int j = bid & 3;
  const int grp = bid >> 2;
  const bool helper = grp == kGroups;
  const int col0 = helper ? kgroup_col(j, 2) * 256 : 0;
  const int row0 = helper ? job_row(0) : grp * 128;
  auto first_loads = [&](int s) {
    const int col = col0 + s * 64;
    expect_load_3d_e(sb + OFF_B + 2 * s * B_SLOT, &mw, sb + BAR_BFULL0 + 2 * s * 8, 0, col, j * 4);
    expect_load_2d_e<false>(sb + OFF_A + s * A_SLOT, &mx64, sb + BAR_AFULL + s * 8, col, row0);
    expect_load_3d_e(sb + OFF_B + (2 * s + 1) * B_SLOT, &mw, sb + BAR_BFULL0 + (2 * s + 1) * 8, 0, col + 32, j * 4);
    expect_load_2d_e<false>(sb + OFF_A + (NA + s) * A_SLOT, &mx64, sb + BAR_AFULL + (NA + s) * 8, col, row0 + 64);
    PROF_ST(2 + s);
  };
  auto init_full = [&](int s) {
    mbar_init(sb + BAR_BFULL0 + 2 * s * 8, 1);
    mbar_init(sb + BAR_BFULL0 + (2 * s + 1) * 8, 1);
    mbar_init(sb + BAR_AFULL + s * 8, 1);
    mbar_init(sb + BAR_AFULL + (NA + s) * 8, 1);
  };
  if (wid == 8) {
    PROF_ST(28);
    if (tid == 256) {
      init_full(0);
      asm volatile("fence.mbarrier_init.release.cluster;" ::: "memory");
    }
    __syncwarp();
    PROF_ST(1);
    first_loads(0);
    if (tid == 256) {
#pragma unroll
      for (int s = 1; s < 4; s++) init_full(s);
      asm volatile("fence.mbarrier_init.release.cluster;" ::: "memory");
    }
    __syncwarp();
#pragma unroll
    for (int s = 1; s < NF; s++) first_loads(s);
  }
  const int wg = wid >> 2;
  const int warp = wid & 3;
  const uint32_t rank = j & 1;
  const int short_t = (gridDim.x > 4 * kGroups && !helper) ? helped_round(grp) * kLayers : -8;
  const unsigned lend = helper ? ~0u : 1u;
  auto moves_up = [&](int t) { return (unsigned)(t + 1 - short_t) > lend; };

  if (wg == 2) {
    asm volatile("setmaxnreg.dec.sync.aligned.u32 40;");
    if (tid == 288) {
      if (sb & 1023) asm volatile("trap;");
#pragma unroll
      for (int i = 0; i < NB; i++) { mbar_init(sb + BAR_BFULL + i * 8, 1); mbar_init(sb + BAR_BEMPTY + i * 8, 2); }
#pragma unroll
      for (int i = 0; i < 4; i++) mbar_init(sb + BAR_XREADY + i * 8, 1);
      mbar_init(sb + BAR_ORDER, 1);
    } else if (tid == 320) {
#pragma unroll
      for (int i = 0; i < 2 * NA; i++) { mbar_init(sb + BAR_AEMPTY + i * 8, 2); mbar_init(sb + BAR_STAGED + i * 8, 4); }
    } else if (tid == 352) {
#pragma unroll
      for (int i = 0; i < 8; i++) { mbar_init(sb + BAR_PFULL + i * 8, 1); mbar_init(sb + BAR_PFREE + i * 8, 1); }
      mbar_init(sb + BAR_BIAS, 32);
      asm volatile("st.shared.v4.f32 [%0], {%1, %1, %1, %1};" ::"r"(sb + OFF_INIT), "f"(kOffset) : "memory");
    }
    asm volatile("fence.mbarrier_init.release.cluster;" ::: "memory");
    __syncwarp();
    cluster_arrive_relaxed();
    if (tid == 288) PROF_ENDS(1000);
    if (warp == 0) {
      PROF_ST(6);
#pragma unroll 1
      for (int s = NF; s < 4; s++) first_loads(s);
      cluster_wait();
      PROF_ST(7);
      uint32_t par = 0;
      int l = 0;
      const int ntiles = helper ? kJobs : kTiles;
#pragma unroll 1
      for (int t = 0; t < ntiles; t++) {
        const int jo = (t == 0 && !helper) ? 0 : j;
        const int q_end = t == short_t ? 2 : 4;
#pragma unroll 1
        for (int q = (helper ? 2 : 0) + (t == 0); q < q_end; q++) {
          const int krow = l * kDim + kgroup_col(jo, q) * 256;
          const bool first = q == (helper ? 2 : 0);
          const bool up = q >= 2 && moves_up(t);
          const int shift = first ? (moves_up(t - 1) ? -1 : 0) : (up && q == 2 ? 1 : 0);
          const int paced = first ? (shift ? DRAIN + 1 : 0) : ((helper || (q == 1 && (t == short_t || t == 0))) ? 0 : NB);
          const uint32_t dst = sb + OFF_B + (up ? B_SLOT : 0);
          const uint32_t full = sb + (first ? BAR_BFULL0 : BAR_BFULL);
          if (shift > 0) mbar_spin(sb + BAR_BEMPTY, par);
#pragma unroll 1
          for (int i = 0; i < NB; i++) {
            if ((unsigned)(i + shift) < NB) mbar_spin(sb + BAR_BEMPTY + (i + shift) * 8, par);
            paced_load_3d_e(dst + i * B_SLOT, &mw, full + i * 8, 0, krow + i * 32, j * 4, i < paced);
            PROF_SKEW(t * 32 + q * 8 + i);
          }
          if (shift < 0) mbar_spin(sb + BAR_BEMPTY + (NB - 1) * 8, par);
          par ^= 1;
        }
        if (helper || ++l == kLayers) l = 0;
      }
    } else if (warp <= 2) {
      const int w = warp - 1;
      const uint32_t abase = sb + OFF_A + w * NA * A_SLOT;
      const uint32_t fullb = sb + BAR_AFULL + w * NA * 8;
      const uint32_t emptyb = sb + BAR_AEMPTY + w * 8;
      const uint32_t stagedb = sb + BAR_STAGED + w * NA * 8;
      const unsigned int base = __shfl_sync(0xffffffffu, *(volatile unsigned int*)(g_flags + (bid * 2 + w) * 32), 0);
      cluster_wait();
      uint32_t epar = 0;
      uint32_t spar = 0;
      auto refill = [&](const CUtensorMap* m, int col, int row) {
#pragma unroll 1
        for (int s = 0; s < 4; s++) {
          mbar_spin(emptyb + s * 16, epar);
          expect_load_2d_e<false>(abase + s * A_SLOT, m, fullb + s * 8, col + s * 64, row);
        }
        epar ^= 1;
      };
      auto store_refill = [&](int out_row, int col, int row, bool last_read) {
#pragma unroll 1
        for (int s = 0; s < 4; s++) {
          mbar_spin(stagedb + s * 8, spar);
          fence_async_smem();
          store_2d_e<true>(&mo64, abase + s * A_SLOT, j * 256 + s * 64, out_row);
          bulk_commit();
          bulk_wait<0>();
          __syncwarp();
          mbar_spin(emptyb + s * 16, epar);
          if (last_read) expect_load_2d_e<true>(abase + s * A_SLOT, &mx64, fullb + s * 8, col + s * 64, row);
          else expect_load_2d_e<false>(abase + s * A_SLOT, &mx64, fullb + s * 8, col + s * 64, row);
        }
        spar ^= 1;
        epar ^= 1;
      };
      auto store_tile = [&](auto stream, int out_row) {
#pragma unroll 1
        for (int c = 0; c < 4; c++) {
          mbar_spin(stagedb + c * 8, spar);
          PROF_EPI(c);
          fence_async_smem();
          arrive_e(fullb + c * 8);
          if (!decltype(stream)::value && w == 1) {
            bulk_commit();
            bulk_wait<0>();
          }
          store_2d_e<decltype(stream)::value>(&mo64, abase + c * A_SLOT, j * 256 + c * 64, out_row);
        }
        spar ^= 1;
        bulk_commit();
        bulk_wait<0>();
        __syncwarp();
      };
      auto refill_shared = [&](const CUtensorMap* m32, int col, int row) {
#pragma unroll 1
        for (int s = 0; s < 4; s++) {
          mbar_spin(emptyb + s * 16, epar);
          expect_load_2d_mc_e(abase + s * A_SLOT + rank * 4096, m32, fullb + s * 8, col + s * 64, row + rank * 32);
        }
        epar ^= 1;
      };
      if (helper) {
#pragma unroll 1
        for (int h = 1; h < 2 * kJobs; h++) refill_shared(&mx32, col0 + (h & 1) * 256, job_row(h >> 1) + w * 64);
      } else {
        const uint32_t xready_peer = map_cta(sb + BAR_XREADY + w * 8, rank ^ 1);
        const unsigned int* oflag = g_flags + ((grp * 4 + kgroup_col(j, 2)) * 2 + w) * 32;
        unsigned int* done_mine = g_flags + kFlagSet + (bid * 2 + w) * 32;
        const unsigned int* done_peer = g_flags + kFlagSet + ((bid ^ 2) * 2 + w) * 32;
        uint32_t nx = 0;
#pragma unroll 1
        for (int rd = 0; rd < kRounds; rd++) {
          const int xrow = (rd * kGroups + grp) * 128 + w * 64;
          if (rd == 0) {
            refill(&mx64, 256, xrow);
          } else {
            poll_flag(done_peer, base + nx);
            store_refill(xrow - kGroups * 128, (j ^ 1) * 256, xrow, rd * kLayers == short_t);
          }
          if (rd * kLayers != short_t) {
#pragma unroll 1
            for (int h = 0; h < 2; h++) refill_shared(&mx32, (kgroup_col(rd == 0 ? 0 : j, 2) + h) * 256, xrow);
          }
#pragma unroll 1
          for (int l = 1; l < kLayers; l++) {
            if (l > 1) poll_flag(done_peer, base + nx);
            store_tile(Flag<false>(), xrow);
            PROF_SVC((rd * kLayers + l - 1) * 2 + w);
            arrive_mapped_e(xready_peer);
            arrive_e(sb + BAR_PUB + w * 8);
            mbar_spin(sb + BAR_XREADY + w * 8, nx & 1);
            fence_async_global();
            refill(&mo64, (j ^ 1) * 256, xrow);
#pragma unroll 1
            for (int h = 0; h < 2; h++) {
              poll_flag(oflag + h * 64, base + nx + 1);
              fence_async_global();
              refill_shared(&mo32, (kgroup_col(j, 2) + h) * 256, xrow);
            }
            if (rank) {
#pragma unroll 1
              for (int s = 0; s < 4; s++) mbar_spin(fullb + s * 8, 1);
            }
            nx++;
            if ((tid & 31) == 0) st_relaxed(done_mine, base + (nx == kRounds * (kLayers - 1) ? kEpoch : nx));
            __syncwarp();
          }
          const int nrow = xrow + kGroups * 128;
          if (rd + 1 == kRounds) {
            poll_flag(done_peer, base + nx);
            store_tile(Flag<true>(), xrow);
            arrive_e(sb + BAR_PUB + w * 8);
          } else {
            refill(&mx64, j * 256, nrow);
          }
          PROF_SVC((rd * kLayers + kLayers - 1) * 2 + w);
        }
      }
    } else {
      const int lane = tid & 31;
      unsigned int* myflag = g_flags + bid * 2 * 32;
      if (lane == 0) { prefetch_map(&mx32); prefetch_map(&mo64); prefetch_map(&mo32); }
      const unsigned int base = *(volatile unsigned int*)myflag;
      auto publish = [&](uint32_t n, uint32_t value) {
#pragma unroll 1
        for (int w = 0; w < 2; w++) {
          mbar_wait(sb + BAR_PUB + w * 8, n & 1);
          asm volatile("fence.acq_rel.gpu;" ::: "memory");
          if (lane == 0) st_relaxed(myflag + w * 32, base + value);
          __syncwarp();
        }
      };
      if (helper) {
        mbar_arrive(sb + BAR_BIAS);
        cluster_wait();
#pragma unroll 1
        for (int n = 0; n < kJobs; n++) {
          if (n + 2 < kJobs) {
            const int row = job_row(n + 2);
#pragma unroll 1
            for (int i = 0; i < 8; i++) prefetch_2d_e(&mx64, col0 + rank * 256 + (i & 3) * 64, row + (i >> 2) * 64);
          }
          publish(n, n + 1);
        }
      } else {
        {
          float c[8];
#pragma unroll
          for (int i = 0; i < 8; i++) c[i] = 0.f;
#pragma unroll 1
          for (int l = 0; l < kLayers; l++) {
            const uint4 v = *reinterpret_cast<const uint4*>(bias + l * kDim + j * 256 + lane * 8);
            const uint32_t u[4] = {v.x, v.y, v.z, v.w};
#pragma unroll
            for (int i = 0; i < 4; i++) {
              c[2 * i] += __uint_as_float(u[i] << 16) + kTrunc;
              c[2 * i + 1] += __uint_as_float(u[i] & 0xffff0000u) + kTrunc;
              uint32_t pk;
              asm("cvt.rn.bf16x2.f32 %0, %1, %2;" : "=r"(pk) : "f"(c[2 * i + 1]), "f"(c[2 * i]));
              asm volatile("st.shared.u32 [%0], %1;" ::"r"(sb + OFF_BIAS + l * 512 + (lane >> 2) * 64 + i * 16 + (lane & 3) * 4),
                           "r"(pk) : "memory");
            }
          }
#pragma unroll
          for (int i = 0; i < 15; i++) {
            const uint32_t one = (lane >> 3) == (lane & 3) ? 0x3f80u << ((lane & 4) * 4) : 0u;
            asm volatile("st.shared.u32 [%0], %1;" ::"r"(sb + OFF_UNIT + i * 128 + lane * 4), "r"(i == 7 ? one : 0u) : "memory");
          }
          fence_async_smem();
          mbar_arrive(sb + BAR_BIAS);
        }
        const __nv_bfloat16* wslice = wptr + bid * 8192;
        cluster_wait();
        prefetch_1d_e(wslice + kDim * kDim, 16384);
        uint32_t nx = 0;
#pragma unroll 1
        for (int rd = 0; rd < kRounds; rd++) {
#pragma unroll 1
          for (int l = 1; l < kLayers; l++) {
            publish(nx, nx + 1 == kRounds * (kLayers - 1) ? kEpoch : nx + 1);
            nx++;
            if (l < kLayers - 1) {
              if (rd == 0) prefetch_1d_e(wslice + (l + 1) * kDim * kDim, 16384);
            } else if (rd + 1 < kRounds) {
              const int nrow = ((rd + 1) * kGroups + grp) * 128;
#pragma unroll 1
              for (int i = 0; i < 8; i++) {
                prefetch_2d_e(&mx64, j * 256 + (i >> 1) * 64, nrow + (i & 1) * 64);
                __nanosleep(300);
              }
              if ((rd + 1) * kLayers == short_t) {
                poll_flag(g_flags + ((4 * kGroups + j) * 2 + 1) * 32, base + job_of_group(grp) + 1);
                fence_async_global();
                constexpr uint32_t order = 0x76325140;
#pragma unroll 1
                for (int i = NP; i < 8; i++)
                  prefetch_2d_e(&mp, j * 256 + ((order >> (i * 4)) & 3) * 64, nrow + ((order >> (i * 4)) & 4) * 16);
#pragma unroll 1
                for (int i = 0; i < 8; i++) {
                  if (i >= NP) mbar_wait(sb + BAR_PFREE + (i - NP) * 8, 0);
                  PROF(776 + i);
                  expect_load_2d_e<true>(sb + OFF_P + (i % NP) * A_SLOT, &mp, sb + BAR_PFULL + i * 8,
                                         j * 256 + ((order >> (i * 4)) & 3) * 64, nrow + ((order >> (i * 4)) & 4) * 16);
                }
              }
            }
          }
        }
#pragma unroll 1
        for (int w = 0; w < 2; w++) mbar_wait(sb + BAR_PUB + w * 8, nx & 1);
      }
    }
    if (warp == (helper ? 3 : 2) && (tid & 31) == 0) PROF_ENDS(1002);
    if (warp == 2) PROF_DUMP();
  } else {
    cluster_arrive_relaxed();
    asm volatile("setmaxnreg.inc.sync.aligned.u32 232;");
    PROF_ST(32);
    const int lane = tid & 31;
    const int wtid = tid & 127;
    const uint32_t abase = sb + OFF_A + wg * NA * A_SLOT;
    const uint32_t afull = sb + BAR_AFULL + wg * NA * 8;
    const uint32_t rel = map_cta(sb + (wtid == 64 ? BAR_BEMPTY : BAR_AEMPTY + wg * 8 - 8), wtid == 32 ? (rank ^ 1) : rank);
    const bool rel_b = wtid == 64;
    const bool rel_ab = (wtid & 31) == 0 && wtid < 96;
    const uint32_t frag0 = __shfl_sync(0xffffffffu, abase + ((wtid >> 5) * 16 + ((lane >> 3) & 1) * 8 + (lane & 7)) * 128 +
                                                        (((lane >> 4) ^ (lane & 7)) << 4), lane);
    const uint64_t adesc0 = desc(((abase & 0x3FFFF) >> 4) | DESC_A_LBO);
    const uint64_t bdesc0 = desc((((sb + OFF_B) & 0x3FFFF) >> 4) | DESC_B_LBO);

    const uint64_t zero = gridDim.y - 1;
    uint64_t adesc_q = adesc0 + zero, bdesc_q = bdesc0 + zero;

    float acc[128];
    uint32_t xr[64];
#pragma unroll
    for (int i = 0; i < 128; i++) acc[i] = kOffset;
#pragma unroll
    for (int i = 0; i < 64; i++) xr[i] = 0;
    int l = 0;
    bool hold = false;
    bool swap = false;
    bool brief = helper;
    int capture_q = helper ? -1 : j;

    auto release = [&](int i, bool with_a) {
      mbar_arrive_mapped_if(rel + i * 8, (i & 1) ? with_a : rel_b);
    };
    auto chunk_staged = [&](int c) {
      __syncwarp();
      arrive_e(sb + BAR_STAGED + (wg * NA + c) * 8);
    };
    auto capture_slot = [&](int p) {
#pragma unroll
      for (int g = 0; g < 4; g++) ldsm4(&xr[(p * 4 + g) * 4], (frag0 ^ (g * 32)) + p * A_SLOT);
    };
    auto swap_half = [&](int p, int half) {
#pragma unroll
      for (int g = half * 2; g < half * 2 + 2; g++) {
        const uint32_t addr = (frag0 ^ (g * 32)) + p * A_SLOT;
        uint32_t n[4];
        ldsm4(n, addr);
        stsm4(addr, &xr[(p * 4 + g) * 4]);
#pragma unroll
        for (int i = 0; i < 4; i++) xr[(p * 4 + g) * 4 + i] = n[i];
      }
      if (half) chunk_staged(p);
    };
    auto chunk_of = [&](int c) { return wg ? (0x7631 >> (c * 4)) & 7 : (0x5420 >> (c * 4)) & 7; };
    auto add_partial = [&](int c) __attribute__((always_inline)) {
      const int n = chunk_of(c);
      const int slot = wg ? (0x1001 >> (c * 4)) & 3 : (0x2120 >> (c * 4)) & 3;
      PROF(768 + wg * 16 + c * 2);
      mbar_spin(sb + BAR_PFULL + n * 8, 0);
      PROF(768 + wg * 16 + c * 2 + 1);
      wg_fence();
      wgmma_n256(acc, ((uint64_t)(128 >> 4) << 32) | ((128 >> 4) << 16) | (((sb + OFF_UNIT + (6 - 2 * c) * 128) & 0x3FFFF) >> 4),
                 ((uint64_t)(256 >> 4) << 32) | ((128 >> 4) << 16) | (((sb + OFF_P + slot * A_SLOT) & 0x3FFFF) >> 4));
    };
    auto issue = [&](int i, int q, int t, bool wait_b) __attribute__((always_inline)) {
      if (!(i & 1)) mbar_spin(afull + (i >> 1) * 8, q & 1);
      if (wait_b) mbar_spin(sb + (q ? BAR_BFULL : BAR_BFULL0) + i * 8, (q ? q ^ t ^ 1 : t) & 1);
      const uint64_t adesc = adesc_q + ((i >> 1) * (A_SLOT >> 4) + (i & 1) * 4);
      const uint64_t bdesc = bdesc_q + i * (B_SLOT >> 4);
      wg_fence();
      wgmma_n256(acc, adesc, bdesc);
      wgmma_n256(acc, adesc + 2, bdesc + 128);
      wg_commit();
      if (i == NB - 1) { adesc_q += zero; bdesc_q += zero; }
    };
    auto retire = [&](int i, bool with_a) {
      wg_wait<2>();
      release((i + 6) & 7, with_a);
    };
    auto k_loop = [&](auto first, int t) __attribute__((always_inline)) {
      constexpr bool FIRST = decltype(first)::value;
      const bool inject = FIRST && brief && !helper;
      const uint32_t up = moves_up(t) ? B_SLOT >> 4 : 0;
      auto extras = [&](int q, int i, bool swap_now) __attribute__((always_inline)) {
        if (!FIRST) return;
        if (swap_now) swap_half(((i + 5) >> 1) & 3, (i + 1) & 1);
        if (!(i & 1) && q == capture_q) capture_slot(i >> 1);
      };
      auto free_partial = [&](int c) {
        if (FIRST) mbar_arrive_if(sb + BAR_PFREE + chunk_of(c) * 8, inject && rel_b);
      };
      extras(0, 0, false);
#pragma unroll
      for (int i = 1; i < 8; i++) {
        if (!(i & 1)) PROF(t * 32 + wg * 16 + 8 + (i >> 1));
        if ((i == 1 || i == 7) && inject) add_partial(i >> 2);
        issue(i, 0, t, true);
        if (i >= 2) retire(i, rel_ab);
        if (i == 3) free_partial(0);
        extras(0, i, i >= 3 && swap);
      }
      PROF(t * 32 + wg * 16 + 1);
      if (!FIRST || !brief) {
#pragma unroll 1
        for (int q = 1; q < 3; q++) {
#pragma unroll
          for (int i = 0; i < 8; i++) {
            issue(i, q | 4, t, true);
            if (i == 0) PROF(t * 32 + wg * 16 + 3 + q);
            retire(i, rel_ab);
            extras(q, i, i < 3 && swap);
          }
          if (FIRST) swap = false;
          if (q == 1) bdesc_q += up;
        }
      }
      const bool rel_last = rel_b | (hold & rel_ab);
      auto with_a = [&](int slot) { return slot == 7 ? rel_ab : rel_last; };
      constexpr int JOIN = DRAIN + 2;
      constexpr int INJ = JOIN < 3 ? 3 : JOIN;
#pragma unroll
      for (int i = 0; i < DRAIN; i++) {
        issue(i, 3, t, true);
        retire(i, with_a((i + 6) & 7));
        if (i == 1) free_partial(1);
        extras(3, i, i < 3 && swap);
      }
      if (wg == 1) {
        wg_wait<1>();
        release((DRAIN + 6) & 7, with_a((DRAIN + 6) & 7));
        wg_wait<0>();
        release((DRAIN + 7) & 7, with_a((DRAIN + 7) & 7));
        if (DRAIN < 2) free_partial(1);
        PROF(t * 32 + wg * 16 + 12);
#pragma unroll
        for (int i = DRAIN; i < 3; i++) extras(-2, i, swap);
        mbar_spin(sb + BAR_ORDER, t & 1);
        PROF(t * 32 + wg * 16 + 6);
#pragma unroll
        for (int i = DRAIN; i < JOIN; i++) {
          issue(i, 3, t, true);
          extras(3, i, false);
        }
      } else {
        PROF(t * 32 + wg * 16 + 6);
#pragma unroll
        for (int i = DRAIN; i < JOIN; i++) {
          issue(i, 3, t, true);
          retire(i, with_a((i + 6) & 7));
          if (i == 1) free_partial(1);
          extras(3, i, i < 3 && swap);
        }
      }
#pragma unroll
      for (int i = JOIN; i < 8; i++) {
        if ((i == INJ || i == 7) && inject) add_partial(i == INJ ? 2 : 3);
        issue(i, 3, t, true);
        if (i == 7) mbar_arrive_if(sb + BAR_ORDER, rel_b & (wg == 0));
        retire(i, rel_last);
        if (i == INJ + 2) free_partial(2);
        extras(3, i, false);
      }
      bdesc_q -= up;
    };

    auto epilogue = [&](auto kind, int t, bool more) __attribute__((always_inline)) {
      constexpr int KIND = decltype(kind)::value;
      constexpr int PRE = KIND == 0 ? BPRE : (KIND == 1 ? HPRE : 0);
      if (KIND != 1 && t == 0) mbar_spin(sb + BAR_BIAS, 0);
      const uint32_t bl = sb + OFF_BIAS + (KIND == 1 ? kLayers - 1 : l) * 512 + ((frag0 >> 3) & 0x30);
      uint32_t bq[8][4];
      auto load_bias = [&](int U) {
        asm volatile("ld.shared.v4.u32 {%0, %1, %2, %3}, [%4];"
                     : "=r"(bq[U][0]), "=r"(bq[U][1]), "=r"(bq[U][2]), "=r"(bq[U][3]) : "r"(bl + U * 64));
      };
#pragma unroll
      for (int U = 0; U < PRE; U++) load_bias(U);
      wg_wait<1>();
      release(6, false);
      if (more) mbar_spin(sb + BAR_BFULL0, (t + 1) & 1);
      wg_wait<0>();
#pragma unroll
      for (int i = 0; i < 128; i++) asm volatile("" : "+f"(acc[i]) :: "memory");
      release(7, KIND == 0 ? rel_b : (KIND == 1 ? rel_ab : rel_b | (more & rel_ab)));
      PROF(t * 32 + wg * 16 + 2);
      if (t == 0) PROF_ST(30 + wg);

      auto pack = [&](int i, float off) {
        uint32_t v;
        asm("cvt.rn.bf16x2.f32 %0, %1, %2;" : "=r"(v) : "f"(acc[i * 2 + 1] - off), "f"(acc[i * 2] - off));
        return v;
      };
      auto cross = [&](int T, int i, float off) {
        uint32_t s2 = pack(T * 4 + i, off), o;
        asm("add.rn.bf16x2 %0, %1, %2;" : "=r"(s2) : "r"(s2), "r"(bq[T >> 1][(T & 1) * 2 + (i >> 1)]));
        asm("fma.rn.bf16x2 %0, %1, %2, %1;" : "=r"(o) : "r"(xr[T * 4 + i]), "r"(s2));
        return o;
      };
      auto reset = [&](int T) {
#pragma unroll
        for (int i = T * 8; i < T * 8 + 8; i += 4)
          asm volatile("ld.volatile.shared.v4.f32 {%0, %1, %2, %3}, [%4];"
                       : "+f"(acc[i]), "+f"(acc[i + 1]), "+f"(acc[i + 2]), "+f"(acc[i + 3]) : "r"(sb + OFF_INIT));
      };
      auto offset_for = [&](int T) { return T >= LAG ? acc[(T - LAG) * 8 + 7] : kOffset; };
      if (KIND == 2) {
        uint32_t id;
        asm volatile("mov.u32 %0, %%tid.x;" : "=r"(id));
        __nv_bfloat16* dst = optr + (size_t)(job_row(t) + wg * 64) * kDim + j * 256 + (id & 127) * 2;
        uint64_t pol;
        asm volatile("createpolicy.fractional.L2::evict_first.b64 %0, 1.0;" : "=l"(pol));
#pragma unroll
        for (int T = 0; T < 16; T++) {
#pragma unroll
          for (int i = 0; i < 4; i++)
            asm volatile("st.global.L2::cache_hint.b32 [%0], %1, %2;"
                         ::"l"(dst + (T * 4 + (i ^ 1)) * kDim), "r"(pack(T * 4 + i, offset_for(T))), "l"(pol) : "memory");
          reset(T);
        }
        asm volatile("bar.sync %0, 128;" ::"r"(wg + 1) : "memory");
        mbar_arrive_if(sb + BAR_PUB + wg * 8, rel_b);
      } else if (KIND == 1) {
#pragma unroll
        for (int T = 0; T < 16; T++) {
#pragma unroll
          for (int i = 0; i < 4; i++) xr[T * 4 + i] = cross(T, i, offset_for(T));
          if ((T & 1) && (T >> 1) + PRE < 8) load_bias((T >> 1) + PRE);
          reset(T);
        }
      } else {
#pragma unroll
        for (int T = 0; T < 16; T++) {
          uint32_t o[4];
#pragma unroll
          for (int i = 0; i < 4; i++) o[i] = cross(T, i, kOffset);
          stsm4((frag0 ^ ((T & 3) * 32)) + (T >> 2) * A_SLOT, o);
          if ((T & 3) == 3) chunk_staged(T >> 2);
          if ((T & 1) && (T >> 1) + PRE < 8) load_bias((T >> 1) + PRE);
        }
        PROF(t * 32 + wg * 16 + 7);
      }
      PROF(t * 32 + wg * 16 + 3);
    };

    PROF_ST(8);
    cluster_wait();
    PROF_ST(9);
    mbar_spin(sb + BAR_BFULL0, 0);
    PROF_ST(10);
    int t = 0;
#pragma unroll 1
    while (true) {
      if (t > 0) {
        if (helper) {
          epilogue(Int<2>(), t - 1, t < kJobs);
          if (t == kJobs) break;
        } else {
          epilogue(Int<1>(), t - 1, true);
        }
      }
      issue(0, 0, 0, false);
      if (t == 0) PROF_ST(11);
      l = 0;
      swap = t > 0 && !helper;
      brief = helper || t == short_t;
      hold = helper && t + 1 < kJobs;
      capture_q = (t > 0 || helper) ? -1 : j;
      PROF(t * 32 + wg * 16 + 0);
      k_loop(Flag<true>(), t);
      t++;
      if (helper) continue;
#pragma unroll 1
      do {
        epilogue(Int<0>(), t - 1, t < kTiles);
        if (t == kTiles) asm volatile("exit;");
        issue(0, 0, 0, false);
        l++;
        hold = l == kLayers - 1 && t + 1 < kTiles;
        PROF(t * 32 + wg * 16 + 0);
        k_loop(Flag<false>(), t);
        t++;
      } while (!hold);
    }
  }
}

__global__ void __launch_bounds__(256) dcn_fallback(const __nv_bfloat16* __restrict__ x0, const __nv_bfloat16* __restrict__ w,
                                                    const __nv_bfloat16* __restrict__ b, __nv_bfloat16* __restrict__ out) {
  __shared__ float xs[8][kDim];
  const size_t r0 = (size_t)blockIdx.x * 8;
  for (int i = threadIdx.x; i < 8 * kDim; i += 256) xs[i / kDim][i % kDim] = __bfloat162float(x0[r0 * kDim + i]);
  __syncthreads();
  for (int l = 0; l < kLayers; l++) {
    float a[4][8] = {};
    for (int k = 0; k < kDim; k++) {
#pragma unroll
      for (int c = 0; c < 4; c++) {
        const float wv = __bfloat162float(w[((size_t)l * kDim + k) * kDim + c * 256 + threadIdx.x]);
#pragma unroll
        for (int r = 0; r < 8; r++) a[c][r] += xs[r][k] * wv;
      }
    }
    __syncthreads();
#pragma unroll
    for (int c = 0; c < 4; c++) {
      const int n = c * 256 + threadIdx.x;
#pragma unroll
      for (int r = 0; r < 8; r++) {
        const float v = __bfloat162float(x0[(r0 + r) * kDim + n]) * (a[c][r] + __bfloat162float(b[l * kDim + n])) + xs[r][n];
        xs[r][n] = __bfloat162float(__float2bfloat16(v));
      }
    }
    __syncthreads();
  }
  for (int i = threadIdx.x; i < 8 * kDim; i += 256) out[r0 * kDim + i] = __float2bfloat16(xs[i / kDim][i % kDim]);
}

typedef CUresult (*EncodeFn)(CUtensorMap*, CUtensorMapDataType, cuuint32_t, void*, const cuuint64_t*, const cuuint64_t*,
                             const cuuint32_t*, const cuuint32_t*, CUtensorMapInterleave, CUtensorMapSwizzle,
                             CUtensorMapL2promotion, CUtensorMapFloatOOBfill);

static void make_map_2d(EncodeFn enc, CUtensorMap* m, void* ptr, uint64_t rows, uint32_t box_rows,
                        CUtensorMapSwizzle swizzle = CU_TENSOR_MAP_SWIZZLE_128B) {
  cuuint64_t dims[2] = {(cuuint64_t)kDim, rows};
  cuuint64_t strides[1] = {kDim * 2};
  cuuint32_t box[2] = {64, box_rows};
  cuuint32_t es[2] = {1, 1};
  enc(m, CU_TENSOR_MAP_DATA_TYPE_BFLOAT16, 2, ptr, dims, strides, box, es, CU_TENSOR_MAP_INTERLEAVE_NONE,
      swizzle, CU_TENSOR_MAP_L2_PROMOTION_L2_128B, CU_TENSOR_MAP_FLOAT_OOB_FILL_NONE);
}

}

extern "C" void kernel_launch(void* const* d_in, const int* in_sizes, int n_in, void* d_out, int out_size) {
  using namespace dcn;
  (void)in_sizes; (void)n_in; (void)out_size;
  void* fn = nullptr;
  cudaDriverEntryPointQueryResult qr;
  cudaGetDriverEntryPoint("cuTensorMapEncodeTiled", &fn, cudaEnableDefault, &qr);
  EncodeFn enc = (EncodeFn)fn;
  CUtensorMap mx64, mx32, mo64, mo32, mw, mp;
  make_map_2d(enc, &mx64, d_in[0], kRows, 64);
  make_map_2d(enc, &mx32, d_in[0], kRows, 32);
  make_map_2d(enc, &mo64, d_out, kRows, 64);
  make_map_2d(enc, &mo32, d_out, kRows, 32);
  make_map_2d(enc, &mp, d_out, kRows, 64, CU_TENSOR_MAP_SWIZZLE_NONE);
  {
    cuuint64_t dims[3] = {64, (cuuint64_t)kLayers * kDim, kDim / 64};
    cuuint64_t strides[2] = {kDim * 2, 128};
    cuuint32_t box[3] = {64, 32, 4};
    cuuint32_t es[3] = {1, 1, 1};
    enc(&mw, CU_TENSOR_MAP_DATA_TYPE_BFLOAT16, 3, d_in[1], dims, strides, box, es, CU_TENSOR_MAP_INTERLEAVE_NONE,
        CU_TENSOR_MAP_SWIZZLE_128B, CU_TENSOR_MAP_L2_PROMOTION_L2_128B, CU_TENSOR_MAP_FLOAT_OOB_FILL_NONE);
  }
  const __nv_bfloat16* x0 = (const __nv_bfloat16*)d_in[0];
  const __nv_bfloat16* w = (const __nv_bfloat16*)d_in[1];
  const __nv_bfloat16* b = (const __nv_bfloat16*)d_in[2];
  __nv_bfloat16* out = (__nv_bfloat16*)d_out;
  constexpr int smem = SMEM_BYTES + PROF_SMEM;
  cudaFuncSetAttribute(dcn_kernel, cudaFuncAttributeMaxDynamicSharedMemorySize, smem);

  cudaLaunchConfig_t cfg = {};
  cfg.gridDim = dim3(4 * kGroups + 4);
  cfg.blockDim = dim3(384);
  cfg.dynamicSmemBytes = smem;
  cudaLaunchAttribute attr;
  attr.id = cudaLaunchAttributeClusterDimension;
  attr.val.clusterDim.x = 2;
  attr.val.clusterDim.y = 1;
  attr.val.clusterDim.z = 1;
  cfg.attrs = &attr;
  cfg.numAttrs = 1;
  int clusters = 0;
  cudaOccupancyMaxActiveClusters(&clusters, dcn_kernel, &cfg);
  if (clusters >= 2 * kGroups) {
    const int grid = 4 * kGroups + (clusters >= 2 * kGroups + 2 ? 4 : 0);
    dcn_kernel<<<grid, 384, smem>>>(x0, w, b, out, mx64, mx32, mo64, mo32, mw, mp);
  } else {
    dcn_fallback<<<kRows / 8, 256>>>(x0, w, b, out);
  }
}
```

```cpp
#include <cuda_runtime.h>
#include <cuda.h>
#include <cuda_bf16.h>
#include <stdint.h>

namespace dcn {

__device__ __forceinline__ void wgmma_n256(float (&d)[128], uint64_t da, uint64_t db) {
  asm volatile("wgmma.mma_async.sync.aligned.m64n256k16.f32.bf16.bf16 "
    "{%0, %1, %2, %3, %4, %5, %6, %7, %8, %9, %10, %11, %12, %13, %14, %15, %16, %17, %18, %19, %20, %21, %22, %23, %24, %25, %26, %27, %28, %29, %30, %31, %32, %33, %34, %35, %36, %37, %38, %39, %40, %41, %42, %43, %44, %45, %46, %47, %48, %49, %50, %51, %52, %53, %54, %55, %56, %57, %58, %59, %60, %61, %62, %63, %64, %65, %66, %67, %68, %69, %70, %71, %72, %73, %74, %75, %76, %77, %78, %79, %80, %81, %82, %83, %84, %85, %86, %87, %88, %89, %90, %91, %92, %93, %94, %95, %96, %97, %98, %99, %100, %101, %102, %103, %104, %105, %106, %107, %108, %109, %110, %111, %112, %113, %114, %115, %116, %117, %118, %119, %120, %121, %122, %123, %124, %125, %126, %127}, "
    "%128, %129, 1, 1, 1, 0, 1;\n"
    : "+f"(d[0]), "+f"(d[1]), "+f"(d[2]), "+f"(d[3]), "+f"(d[4]), "+f"(d[5]), "+f"(d[6]), "+f"(d[7]), "+f"(d[8]), "+f"(d[9]), "+f"(d[10]), "+f"(d[11]), "+f"(d[12]), "+f"(d[13]), "+f"(d[14]), "+f"(d[15]), "+f"(d[16]), "+f"(d[17]), "+f"(d[18]), "+f"(d[19]), "+f"(d[20]), "+f"(d[21]), "+f"(d[22]), "+f"(d[23]), "+f"(d[24]), "+f"(d[25]), "+f"(d[26]), "+f"(d[27]), "+f"(d[28]), "+f"(d[29]), "+f"(d[30]), "+f"(d[31]), "+f"(d[32]), "+f"(d[33]), "+f"(d[34]), "+f"(d[35]), "+f"(d[36]), "+f"(d[37]), "+f"(d[38]), "+f"(d[39]), "+f"(d[40]), "+f"(d[41]), "+f"(d[42]), "+f"(d[43]), "+f"(d[44]), "+f"(d[45]), "+f"(d[46]), "+f"(d[47]), "+f"(d[48]), "+f"(d[49]), "+f"(d[50]), "+f"(d[51]), "+f"(d[52]), "+f"(d[53]), "+f"(d[54]), "+f"(d[55]), "+f"(d[56]), "+f"(d[57]), "+f"(d[58]), "+f"(d[59]), "+f"(d[60]), "+f"(d[61]), "+f"(d[62]), "+f"(d[63]), "+f"(d[64]), "+f"(d[65]), "+f"(d[66]), "+f"(d[67]), "+f"(d[68]), "+f"(d[69]), "+f"(d[70]), "+f"(d[71]), "+f"(d[72]), "+f"(d[73]), "+f"(d[74]), "+f"(d[75]), "+f"(d[76]), "+f"(d[77]), "+f"(d[78]), "+f"(d[79]), "+f"(d[80]), "+f"(d[81]), "+f"(d[82]), "+f"(d[83]), "+f"(d[84]), "+f"(d[85]), "+f"(d[86]), "+f"(d[87]), "+f"(d[88]), "+f"(d[89]), "+f"(d[90]), "+f"(d[91]), "+f"(d[92]), "+f"(d[93]), "+f"(d[94]), "+f"(d[95]), "+f"(d[96]), "+f"(d[97]), "+f"(d[98]), "+f"(d[99]), "+f"(d[100]), "+f"(d[101]), "+f"(d[102]), "+f"(d[103]), "+f"(d[104]), "+f"(d[105]), "+f"(d[106]), "+f"(d[107]), "+f"(d[108]), "+f"(d[109]), "+f"(d[110]), "+f"(d[111]), "+f"(d[112]), "+f"(d[113]), "+f"(d[114]), "+f"(d[115]), "+f"(d[116]), "+f"(d[117]), "+f"(d[118]), "+f"(d[119]), "+f"(d[120]), "+f"(d[121]), "+f"(d[122]), "+f"(d[123]), "+f"(d[124]), "+f"(d[125]), "+f"(d[126]), "+f"(d[127])
    : "l"(da), "l"(db));
}

constexpr int kDim = 1024;
constexpr int kRows = 16384;
constexpr int kLayers = 6;
constexpr int kGroups = 32;
constexpr int kRounds = kRows / 128 / kGroups;
constexpr int kTiles = kRounds * kLayers;

constexpr int kJobs = kGroups;
constexpr int kEpoch = 32;
constexpr int NA = 4;
constexpr int NB = 8;
constexpr float kOffset = 85.333336f;
constexpr float kTrunc = 64 * 0.375f / 131072;
constexpr int DRAIN = 1;
constexpr int LAG = 3;
constexpr int BPRE = 5;
constexpr int HPRE = 6;
constexpr int NF = 2;
constexpr int A_SLOT = 8192;
constexpr int B_SLOT = 16384;
constexpr int OFF_B = 0;
constexpr int NP = 3;
constexpr int OFF_P = OFF_B + NB * B_SLOT;
constexpr int OFF_A = OFF_P + NP * A_SLOT;
constexpr int OFF_UNIT = OFF_A + 2 * NA * A_SLOT;
constexpr int OFF_BIAS = OFF_UNIT + 2048;
constexpr int OFF_INIT = OFF_BIAS + kLayers * 256 * 2;
constexpr int OFF_BAR = OFF_INIT + 16;
constexpr int BAR_BFULL = OFF_BAR;
constexpr int BAR_BFULL0 = BAR_BFULL + NB * 8;
constexpr int BAR_BEMPTY = BAR_BFULL0 + NB * 8;
constexpr int BAR_AFULL = BAR_BEMPTY + NB * 8;
constexpr int BAR_AEMPTY = BAR_AFULL + 2 * NA * 8;
constexpr int BAR_XREADY = BAR_AEMPTY + 2 * NA * 8;
constexpr int BAR_PUB = BAR_XREADY + 16;
constexpr int BAR_PFULL = BAR_PUB + 16;
constexpr int BAR_PFREE = BAR_PFULL + 8 * 8;
constexpr int BAR_STAGED = BAR_PFREE + 8 * 8;
constexpr int BAR_ORDER = BAR_STAGED + 2 * NA * 8;
constexpr int BAR_BIAS = BAR_ORDER + 8;
constexpr int SMEM_BYTES = BAR_BIAS + 8;
static_assert(SMEM_BYTES <= 232448, "shared memory budget");

constexpr int kFlagSet = 4 * (kGroups + 1) * 32;
__device__ unsigned int g_flags[3 * kFlagSet];

__device__ __forceinline__ uint32_t smem_u32(const void* p) { return (uint32_t)__cvta_generic_to_shared(p); }
__device__ __forceinline__ void mbar_init(uint32_t bar, int cnt) {
  asm volatile("mbarrier.init.shared::cta.b64 [%0], %1;" ::"r"(bar), "r"(cnt) : "memory");
}
__device__ __forceinline__ void mbar_arrive(uint32_t bar) {
  asm volatile("mbarrier.arrive.shared::cta.b64 _, [%0];" ::"r"(bar) : "memory");
}
__device__ __forceinline__ uint32_t map_cta(uint32_t addr, uint32_t cta) {
  uint32_t r;
  asm volatile("mapa.shared::cluster.u32 %0, %1, %2;" : "=r"(r) : "r"(addr), "r"(cta));
  return r;
}
__device__ __forceinline__ void mbar_arrive_mapped_if(uint32_t cluster_addr, bool pred) {
  asm volatile("{\n.reg .pred p;\nsetp.ne.u32 p, %1, 0;\n@p mbarrier.arrive.shared::cluster.b64 _, [%0];\n}"
               ::"r"(cluster_addr), "r"((uint32_t)pred) : "memory");
}
__device__ __forceinline__ void mbar_arrive_if(uint32_t bar, bool pred) {
  asm volatile("{\n.reg .pred p;\nsetp.ne.u32 p, %1, 0;\n@p mbarrier.arrive.shared::cta.b64 _, [%0];\n}"
               ::"r"(bar), "r"((uint32_t)pred) : "memory");
}
__device__ __forceinline__ void mbar_wait(uint32_t bar, uint32_t parity) {
  asm volatile(
      "{\n.reg .pred p;\n.reg .u32 c;\n"
      "mbarrier.try_wait.parity.shared::cta.b64 p, [%0], %1;\n"
      "@p bra DONE;\n"
      "mov.u32 c, 0;\n"
      "LOOP:\n"
      "mbarrier.try_wait.parity.shared::cta.b64 p, [%0], %1;\n"
      "@p bra DONE;\n"
      "add.u32 c, c, 1;\n"
      "setp.lt.u32 p, c, 1048576;\n"
      "@p bra LOOP;\n"
      "trap;\n"
      "DONE:\n}"
      ::"r"(bar), "r"(parity) : "memory");
}
__device__ __forceinline__ void mbar_spin(uint32_t bar, uint32_t parity) {
  asm volatile(
      "{\n.reg .pred p;\n"
      "LOOP:\n"
      "mbarrier.try_wait.parity.shared::cta.b64 p, [%0], %1;\n"
      "@!p bra LOOP;\n}"
      ::"r"(bar), "r"(parity) : "memory");
}
#define ELECT_BEGIN "{\n.reg .pred e;\nelect.sync _|e, 0xffffffff;\n"
template <bool STREAM> __device__ __forceinline__ void expect_load_2d_e(uint32_t dst, const CUtensorMap* m, uint32_t bar, int c0, int c1) {
  if (STREAM) {
    asm volatile(ELECT_BEGIN ".reg .b64 pol;\ncreatepolicy.fractional.L2::evict_first.b64 pol, 1.0;\n"
                 "@e mbarrier.arrive.expect_tx.shared::cta.b64 _, [%2], 8192;\n"
                 "@e cp.async.bulk.tensor.2d.shared::cluster.global.mbarrier::complete_tx::bytes.L2::cache_hint [%0], [%1, {%3, %4}], [%2], pol;\n}"
                 ::"r"(dst), "l"(m), "r"(bar), "r"(c0), "r"(c1) : "memory");
  } else {
    asm volatile(ELECT_BEGIN
                 "@e mbarrier.arrive.expect_tx.shared::cta.b64 _, [%2], 8192;\n"
                 "@e cp.async.bulk.tensor.2d.shared::cluster.global.mbarrier::complete_tx::bytes [%0], [%1, {%3, %4}], [%2];\n}"
                 ::"r"(dst), "l"(m), "r"(bar), "r"(c0), "r"(c1) : "memory");
  }
}
__device__ __forceinline__ void expect_load_2d_mc_e(uint32_t dst, const CUtensorMap* m, uint32_t bar, int c0, int c1) {
  asm volatile(ELECT_BEGIN ".reg .b64 pol;\ncreatepolicy.fractional.L2::evict_first.b64 pol, 1.0;\n"
               "@e mbarrier.arrive.expect_tx.shared::cta.b64 _, [%2], 8192;\n"
               "@e cp.async.bulk.tensor.2d.shared::cluster.global.mbarrier::complete_tx::bytes.multicast::cluster.L2::cache_hint [%0], [%1, {%3, %4}], [%2], %5, pol;\n}"
               ::"r"(dst), "l"(m), "r"(bar), "r"(c0), "r"(c1), "h"((uint16_t)3) : "memory");
}
__device__ __forceinline__ void expect_load_3d_e(uint32_t dst, const CUtensorMap* m, uint32_t bar, int c0, int c1, int c2) {
  asm volatile(ELECT_BEGIN
               "@e mbarrier.arrive.expect_tx.shared::cta.b64 _, [%2], 16384;\n"
               "@e cp.async.bulk.tensor.3d.shared::cluster.global.mbarrier::complete_tx::bytes [%0], [%1, {%3, %4, %5}], [%2];\n}"
               ::"r"(dst), "l"(m), "r"(bar), "r"(c0), "r"(c1), "r"(c2) : "memory");
}
template <bool STREAM> __device__ __forceinline__ void store_2d_e(const CUtensorMap* m, uint32_t src, int c0, int c1) {
  if (STREAM) {
    asm volatile(ELECT_BEGIN ".reg .b64 pol;\ncreatepolicy.fractional.L2::evict_first.b64 pol, 1.0;\n"
                 "@e cp.async.bulk.tensor.2d.global.shared::cta.bulk_group.L2::cache_hint [%0, {%2, %3}], [%1], pol;\n}"
                 ::"l"(m), "r"(src), "r"(c0), "r"(c1) : "memory");
  } else {
    asm volatile(ELECT_BEGIN
                 "@e cp.async.bulk.tensor.2d.global.shared::cta.bulk_group [%0, {%2, %3}], [%1];\n}"
                 ::"l"(m), "r"(src), "r"(c0), "r"(c1) : "memory");
  }
}
__device__ __forceinline__ void prefetch_2d_e(const CUtensorMap* m, int c0, int c1) {
  asm volatile(ELECT_BEGIN
               "@e cp.async.bulk.prefetch.tensor.2d.L2.global [%0, {%1, %2}];\n}"
               ::"l"(m), "r"(c0), "r"(c1) : "memory");
}
__device__ __forceinline__ void prefetch_1d_e(const void* ptr, uint32_t bytes) {
  asm volatile(ELECT_BEGIN
               "@e cp.async.bulk.prefetch.L2.global [%0], %1;\n}"
               ::"l"(ptr), "r"(bytes) : "memory");
}
__device__ __forceinline__ void paced_load_3d_e(uint32_t dst, const CUtensorMap* m, uint32_t bar, int c0, int c1, int c2, bool pace) {
  asm volatile(ELECT_BEGIN ".reg .pred p;\nsetp.ne.u32 p, %6, 0;\n"
               "@e mbarrier.arrive.expect_tx.shared::cta.b64 _, [%2], 16384;\n"
               "@p nanosleep.u32 128;\n"
               "@e cp.async.bulk.tensor.3d.shared::cluster.global.mbarrier::complete_tx::bytes [%0], [%1, {%3, %4, %5}], [%2];\n}"
               ::"r"(dst), "l"(m), "r"(bar), "r"(c0), "r"(c1), "r"(c2), "r"((uint32_t)pace) : "memory");
}
__device__ __forceinline__ void arrive_mapped_e(uint32_t cluster_addr) {
  asm volatile(ELECT_BEGIN "@e mbarrier.arrive.shared::cluster.b64 _, [%0];\n}" ::"r"(cluster_addr) : "memory");
}
__device__ __forceinline__ void arrive_e(uint32_t bar) {
  asm volatile(ELECT_BEGIN "@e mbarrier.arrive.shared::cta.b64 _, [%0];\n}" ::"r"(bar) : "memory");
}
__device__ __forceinline__ void bulk_commit() { asm volatile("cp.async.bulk.commit_group;" ::: "memory"); }
template <int N> __device__ __forceinline__ void bulk_wait() { asm volatile("cp.async.bulk.wait_group %0;" ::"n"(N) : "memory"); }
__device__ __forceinline__ void wg_fence() { asm volatile("wgmma.fence.sync.aligned;" ::: "memory"); }
__device__ __forceinline__ void wg_commit() { asm volatile("wgmma.commit_group.sync.aligned;" ::: "memory"); }
template <int N> __device__ __forceinline__ void wg_wait() { asm volatile("wgmma.wait_group.sync.aligned %0;" ::"n"(N) : "memory"); }
__device__ __forceinline__ void fence_async_global() { asm volatile("fence.proxy.async.global;" ::: "memory"); }
__device__ __forceinline__ void st_relaxed(unsigned int* p, unsigned int v) {
  asm volatile("st.relaxed.gpu.global.u32 [%0], %1;" ::"l"(p), "r"(v) : "memory");
}
__device__ __forceinline__ void ldsm4(uint32_t* r, uint32_t addr) {
  asm volatile("ldmatrix.sync.aligned.m8n8.x4.shared.b16 {%0, %1, %2, %3}, [%4];"
               : "=r"(r[0]), "=r"(r[1]), "=r"(r[2]), "=r"(r[3]) : "r"(addr) : "memory");
}
__device__ __forceinline__ void stsm4(uint32_t addr, const uint32_t* r) {
  asm volatile("stmatrix.sync.aligned.m8n8.x4.shared.b16 [%0], {%1, %2, %3, %4};"
               ::"r"(addr), "r"(r[0]), "r"(r[1]), "r"(r[2]), "r"(r[3]) : "memory");
}
template <bool V> struct Flag { static constexpr bool value = V; };
template <int V> struct Int { static constexpr int value = V; };
__device__ __forceinline__ void fence_async_smem() { asm volatile("fence.proxy.async.shared::cta;" ::: "memory"); }
__device__ __forceinline__ void cluster_arrive_relaxed() { asm volatile("barrier.cluster.arrive.relaxed.aligned;" ::: "memory"); }
__device__ __forceinline__ void cluster_wait() { asm volatile("barrier.cluster.wait.acquire.aligned;" ::: "memory"); }
__device__ __forceinline__ void prefetch_map(const CUtensorMap* m) {
  asm volatile("prefetch.tensormap [%0];" ::"l"(m) : "memory");
}
__device__ __forceinline__ void prefetch_map_e(const CUtensorMap* m) {
  asm volatile(ELECT_BEGIN "@e prefetch.tensormap [%0];\n}" ::"l"(m) : "memory");
}
__device__ __forceinline__ void poll_flag(const unsigned int* ptr, unsigned int target) {
  asm volatile(
      "{\n.reg .pred p;\n.reg .u32 c;\n.reg .s32 v;\n"
      "mov.u32 c, 0;\n"
      "LOOP:\n"
      "ld.acquire.gpu.global.s32 v, [%0];\n"
      "sub.s32 v, v, %1;\n"
      "setp.ge.s32 p, v, 0;\n"
      "@p bra DONE;\n"
      "add.u32 c, c, 1;\n"
      "setp.lt.u32 p, c, 1048576;\n"
      "@p bra LOOP;\n"
      "trap;\n"
      "DONE:\n}"
      ::"l"(ptr), "r"(target) : "memory");
}

constexpr uint32_t DESC_HI = (1024u >> 4) | (1u << 30);
__device__ __forceinline__ uint64_t desc(uint32_t lo) { return ((uint64_t)DESC_HI << 32) | lo; }
constexpr uint32_t DESC_A_LBO = 1u << 16;
constexpr uint32_t DESC_B_LBO = (4096u >> 4) << 16;

__device__ __forceinline__ int kgroup_col(int j, int q) {
  return q == 0 ? j : (q == 1 ? (j ^ 1) : (((j ^ 2) & ~1) + (q - 2)));
}

__device__ __forceinline__ int role_of_cluster(int c) {
  const int a = c - 4;
  const int b = c - 36, r = (b * 37) >> 8;
  const int first = (a & ~7) + (a & 3) * 2 + ((a >> 2) & 1);
  const int second = 32 + r * 8 + ((0x7531640 >> (((b - r * 7) * 4) & 31)) & 7);
  return c >= 2 * kGroups ? c : (c >= 36 ? second : (c >= 4 ? first : 34 + c * 8));
}
__device__ __forceinline__ int helped_round(int grp) { return (grp & 2) ? (grp & 3) - 1 : 3; }
__device__ __forceinline__ int job_of_group(int grp) {
  return (grp & 2) ? (grp & 1) * 8 + (grp >> 2) : 16 + (grp >> 2) * 2 + (grp & 1);
}
__device__ __forceinline__ int job_row(int n) {
  const int grp = n < 16 ? (n & 7) * 4 + 2 + (n >> 3) : ((n - 16) >> 1) * 4 + (n & 1);
  return (helped_round(grp) * kGroups + grp) * 128;
}

#define PROF_ENDS(idx) do {} while (0)
#define PROF_SVC(idx) do {} while (0)
#define PROF_ST(idx) do {} while (0)
#define PROF_EPI(c) do {} while (0)
#define PROF_SKEW(idx) do {} while (0)
#define PROF(idx) do {} while (0)
#define PROF_DUMP() do {} while (0)
constexpr int PROF_SMEM = 0;

__global__ void __cluster_dims__(2, 1, 1) __launch_bounds__(384, 1)
dcn_kernel(const __nv_bfloat16* __restrict__ xptr, const __nv_bfloat16* __restrict__ wptr,
           const __nv_bfloat16* __restrict__ bias, __nv_bfloat16* optr,
           const __grid_constant__ CUtensorMap mx64, const __grid_constant__ CUtensorMap mx32,
           const __grid_constant__ CUtensorMap mo64, const __grid_constant__ CUtensorMap mo32,
           const __grid_constant__ CUtensorMap mw, const __grid_constant__ CUtensorMap mp) {
  extern __shared__ __align__(1024) uint8_t smem_raw[];
  const uint32_t sb = smem_u32(smem_raw);
  const int tid = threadIdx.x;
  if ((tid >> 5) == 8) PROF_ST(0);
  const int wid = __shfl_sync(0xffffffffu, tid >> 5, 0);
  if (wid == 0) {
    asm volatile("prefetch.global.L2 [%0];" ::"l"(wptr + ((blockIdx.x & 31) * 32 + tid) * 64));
    asm volatile("prefetch.global.L2 [%0];" ::"l"(xptr + ((blockIdx.x & 127) * 32 + tid) * kDim));
    prefetch_map_e(&mw);
    prefetch_map_e(&mx64);
    PROF_ST(29);
  }
  const int bid = role_of_cluster(blockIdx.x >> 1) * 2 + (blockIdx.x & 1);
  const int j = bid & 3;
  const int grp = bid >> 2;
  const bool helper = grp == kGroups;
  const int col0 = helper ? kgroup_col(j, 2) * 256 : 0;
  const int row0 = helper ? job_row(0) : grp * 128;
  auto first_loads = [&](int s) {
    const int col = col0 + s * 64;
    expect_load_3d_e(sb + OFF_B + 2 * s * B_SLOT, &mw, sb + BAR_BFULL0 + 2 * s * 8, 0, col, j * 4);
    expect_load_2d_e<false>(sb + OFF_A + s * A_SLOT, &mx64, sb + BAR_AFULL + s * 8, col, row0);
    expect_load_3d_e(sb + OFF_B + (2 * s + 1) * B_SLOT, &mw, sb + BAR_BFULL0 + (2 * s + 1) * 8, 0, col + 32, j * 4);
    expect_load_2d_e<false>(sb + OFF_A + (NA + s) * A_SLOT, &mx64, sb + BAR_AFULL + (NA + s) * 8, col, row0 + 64);
    PROF_ST(2 + s);
  };
  auto init_full = [&](int s) {
    mbar_init(sb + BAR_BFULL0 + 2 * s * 8, 1);
    mbar_init(sb + BAR_BFULL0 + (2 * s + 1) * 8, 1);
    mbar_init(sb + BAR_AFULL + s * 8, 1);
    mbar_init(sb + BAR_AFULL + (NA + s) * 8, 1);
  };
  if (wid == 8) {
    PROF_ST(28);
    if (tid == 256) {
      init_full(0);
      asm volatile("fence.mbarrier_init.release.cluster;" ::: "memory");
    }
    __syncwarp();
    PROF_ST(1);
    first_loads(0);
    if (tid == 256) {
#pragma unroll
      for (int s = 1; s < 4; s++) init_full(s);
      asm volatile("fence.mbarrier_init.release.cluster;" ::: "memory");
    }
    __syncwarp();
#pragma unroll
    for (int s = 1; s < NF; s++) first_loads(s);
  }
  const int wg = wid >> 2;
  const int warp = wid & 3;
  const uint32_t rank = j & 1;
  const int short_t = (gridDim.x > 4 * kGroups && !helper) ? helped_round(grp) * kLayers : -8;
  const unsigned lend = helper ? ~0u : 1u;
  auto moves_up = [&](int t) { return (unsigned)(t + 1 - short_t) > lend; };

  if (wg == 2) {
    asm volatile("setmaxnreg.dec.sync.aligned.u32 40;");
    if (tid == 288) {
      if (sb & 1023) asm volatile("trap;");
#pragma unroll
      for (int i = 0; i < NB; i++) { mbar_init(sb + BAR_BFULL + i * 8, 1); mbar_init(sb + BAR_BEMPTY + i * 8, 2); }
#pragma unroll
      for (int i = 0; i < 4; i++) mbar_init(sb + BAR_XREADY + i * 8, 1);
      mbar_init(sb + BAR_ORDER, 1);
    } else if (tid == 320) {
#pragma unroll
      for (int i = 0; i < 2 * NA; i++) { mbar_init(sb + BAR_AEMPTY + i * 8, 2); mbar_init(sb + BAR_STAGED + i * 8, 4); }
    } else if (tid == 352) {
#pragma unroll
      for (int i = 0; i < 8; i++) { mbar_init(sb + BAR_PFULL + i * 8, 1); mbar_init(sb + BAR_PFREE + i * 8, 1); }
      mbar_init(sb + BAR_BIAS, 32);
      asm volatile("st.shared.v4.f32 [%0], {%1, %1, %1, %1};" ::"r"(sb + OFF_INIT), "f"(kOffset) : "memory");
    }
    asm volatile("fence.mbarrier_init.release.cluster;" ::: "memory");
    __syncwarp();
    cluster_arrive_relaxed();
    if (tid == 288) PROF_ENDS(1000);
    if (warp == 0) {
      PROF_ST(6);
#pragma unroll 1
      for (int s = NF; s < 4; s++) first_loads(s);
      cluster_wait();
      PROF_ST(7);
      uint32_t par = 0;
      int l = 0;
      const int ntiles = helper ? kJobs : kTiles;
#pragma unroll 1
      for (int t = 0; t < ntiles; t++) {
        const int jo = (t == 0 && !helper) ? 0 : j;
        const int q_end = t == short_t ? 2 : 4;
#pragma unroll 1
        for (int q = (helper ? 2 : 0) + (t == 0); q < q_end; q++) {
          const int krow = l * kDim + kgroup_col(jo, q) * 256;
          const bool first = q == (helper ? 2 : 0);
          const bool up = q >= 2 && moves_up(t);
          const int shift = first ? (moves_up(t - 1) ? -1 : 0) : (up && q == 2 ? 1 : 0);
          const int paced = first ? (shift ? DRAIN + 1 : 0) : ((helper || (q == 1 && (t == short_t || t == 0))) ? 0 : NB);
          const uint32_t dst = sb + OFF_B + (up ? B_SLOT : 0);
          const uint32_t full = sb + (first ? BAR_BFULL0 : BAR_BFULL);
          if (shift > 0) mbar_spin(sb + BAR_BEMPTY, par);
#pragma unroll 1
          for (int i = 0; i < NB; i++) {
            if ((unsigned)(i + shift) < NB) mbar_spin(sb + BAR_BEMPTY + (i + shift) * 8, par);
            paced_load_3d_e(dst + i * B_SLOT, &mw, full + i * 8, 0, krow + i * 32, j * 4, i < paced);
            PROF_SKEW(t * 32 + q * 8 + i);
          }
          if (shift < 0) mbar_spin(sb + BAR_BEMPTY + (NB - 1) * 8, par);
          par ^= 1;
        }
        if (helper || ++l == kLayers) l = 0;
      }
    } else if (warp <= 2) {
      const int w = warp - 1;
      const uint32_t abase = sb + OFF_A + w * NA * A_SLOT;
      const uint32_t fullb = sb + BAR_AFULL + w * NA * 8;
      const uint32_t emptyb = sb + BAR_AEMPTY + w * 8;
      const uint32_t stagedb = sb + BAR_STAGED + w * NA * 8;
      const unsigned int base = __shfl_sync(0xffffffffu, *(volatile unsigned int*)(g_flags + bid * 32), 0);
      cluster_wait();
      uint32_t epar = 0;
      uint32_t spar = 0;
      auto refill = [&](const CUtensorMap* m, int col, int row) {
#pragma unroll 1
        for (int s = 0; s < 4; s++) {
          mbar_spin(emptyb + s * 16, epar);
          expect_load_2d_e<false>(abase + s * A_SLOT, m, fullb + s * 8, col + s * 64, row);
        }
        epar ^= 1;
      };
      auto store_refill = [&](int out_row, int col, int row, bool last_read) {
#pragma unroll 1
        for (int s = 0; s < 4; s++) {
          mbar_spin(stagedb + s * 8, spar);
          fence_async_smem();
          store_2d_e<true>(&mo64, abase + s * A_SLOT, j * 256 + s * 64, out_row);
          bulk_commit();
          bulk_wait<0>();
          __syncwarp();
          mbar_spin(emptyb + s * 16, epar);
          if (last_read) expect_load_2d_e<true>(abase + s * A_SLOT, &mx64, fullb + s * 8, col + s * 64, row);
          else expect_load_2d_e<false>(abase + s * A_SLOT, &mx64, fullb + s * 8, col + s * 64, row);
        }
        spar ^= 1;
        epar ^= 1;
      };
      auto store_tile = [&](auto stream, int out_row) {
#pragma unroll 1
        for (int c = 0; c < 4; c++) {
          mbar_spin(stagedb + c * 8, spar);
          PROF_EPI(c);
          fence_async_smem();
          arrive_e(fullb + c * 8);
          if (!decltype(stream)::value && w == 1) {
            bulk_commit();
            bulk_wait<0>();
          }
          store_2d_e<decltype(stream)::value>(&mo64, abase + c * A_SLOT, j * 256 + c * 64, out_row);
        }
        spar ^= 1;
        bulk_commit();
        bulk_wait<0>();
        __syncwarp();
      };
      auto refill_shared = [&](const CUtensorMap* m32, int col, int row) {
#pragma unroll 1
        for (int s = 0; s < 4; s++) {
          mbar_spin(emptyb + s * 16, epar);
          expect_load_2d_mc_e(abase + s * A_SLOT + rank * 4096, m32, fullb + s * 8, col + s * 64, row + rank * 32);
        }
        epar ^= 1;
      };
      if (helper) {
#pragma unroll 1
        for (int h = 1; h < 2 * kJobs; h++) refill_shared(&mx32, col0 + (h & 1) * 256, job_row(h >> 1) + w * 64);
      } else {
        const uint32_t xready_peer = map_cta(sb + BAR_XREADY + w * 8, rank ^ 1);
        const unsigned int* oflag = g_flags + (grp * 4 + kgroup_col(j, 2)) * 32;
        unsigned int* done_mine = g_flags + kFlagSet + (bid * 2 + w) * 32;
        const unsigned int* done_peer = g_flags + kFlagSet + ((bid ^ 2) * 2 + w) * 32;
        uint32_t nx = 0;
#pragma unroll 1
        for (int rd = 0; rd < kRounds; rd++) {
          const int xrow = (rd * kGroups + grp) * 128 + w * 64;
          if (rd == 0) {
            refill(&mx64, 256, xrow);
          } else {
            poll_flag(done_peer, base + nx);
            store_refill(xrow - kGroups * 128, (j ^ 1) * 256, xrow, rd * kLayers == short_t);
          }
          if (rd * kLayers != short_t) {
#pragma unroll 1
            for (int h = 0; h < 2; h++) refill_shared(&mx32, (kgroup_col(rd == 0 ? 0 : j, 2) + h) * 256, xrow);
          }
#pragma unroll 1
          for (int l = 1; l < kLayers; l++) {
            if (l > 1) poll_flag(done_peer, base + nx);
            store_tile(Flag<false>(), xrow);
            PROF_SVC((rd * kLayers + l - 1) * 2 + w);
            arrive_mapped_e(xready_peer);
            arrive_e(sb + BAR_PUB + w * 8);
            mbar_spin(sb + BAR_XREADY + w * 8, nx & 1);
            fence_async_global();
            refill(&mo64, (j ^ 1) * 256, xrow);
#pragma unroll 1
            for (int h = 0; h < 2; h++) {
              poll_flag(oflag + h * 32, base + nx + 1);
              fence_async_global();
              refill_shared(&mo32, (kgroup_col(j, 2) + h) * 256, xrow);
            }
            if (rank) {
#pragma unroll 1
              for (int s = 0; s < 4; s++) mbar_spin(fullb + s * 8, 1);
            }
            nx++;
            if ((tid & 31) == 0) st_relaxed(done_mine, base + (nx == kRounds * (kLayers - 1) ? kEpoch : nx));
            __syncwarp();
          }
          const int nrow = xrow + kGroups * 128;
          if (rd + 1 == kRounds) {
            poll_flag(done_peer, base + nx);
            store_tile(Flag<true>(), xrow);
            arrive_e(sb + BAR_PUB + w * 8);
          } else {
            refill(&mx64, j * 256, nrow);
          }
          PROF_SVC((rd * kLayers + kLayers - 1) * 2 + w);
        }
      }
    } else {
      const int lane = tid & 31;
      unsigned int* myflag = g_flags + bid * 32;
      if (lane == 0) { prefetch_map(&mx32); prefetch_map(&mo64); prefetch_map(&mo32); }
      const unsigned int base = *(volatile unsigned int*)myflag;
      auto publish = [&](uint32_t n, uint32_t value) {
#pragma unroll 1
        for (int w = 0; w < 2; w++) mbar_wait(sb + BAR_PUB + w * 8, n & 1);
        if (lane == 0) asm volatile("st.release.gpu.global.u32 [%0], %1;" ::"l"(myflag), "r"(base + value) : "memory");
        __syncwarp();
      };
      if (helper) {
        mbar_arrive(sb + BAR_BIAS);
        cluster_wait();
#pragma unroll 1
        for (int n = 0; n < kJobs; n++) {
          if (n + 2 < kJobs) {
            const int row = job_row(n + 2);
#pragma unroll 1
            for (int i = 0; i < 8; i++) prefetch_2d_e(&mx64, col0 + rank * 256 + (i & 3) * 64, row + (i >> 2) * 64);
          }
          publish(n, n + 1);
        }
      } else {
        {
          float c[8];
#pragma unroll
          for (int i = 0; i < 8; i++) c[i] = 0.f;
#pragma unroll 1
          for (int l = 0; l < kLayers; l++) {
            const uint4 v = *reinterpret_cast<const uint4*>(bias + l * kDim + j * 256 + lane * 8);
            const uint32_t u[4] = {v.x, v.y, v.z, v.w};
#pragma unroll
            for (int i = 0; i < 4; i++) {
              c[2 * i] += __uint_as_float(u[i] << 16) + kTrunc;
              c[2 * i + 1] += __uint_as_float(u[i] & 0xffff0000u) + kTrunc;
              uint32_t pk;
              asm("cvt.rn.bf16x2.f32 %0, %1, %2;" : "=r"(pk) : "f"(c[2 * i + 1]), "f"(c[2 * i]));
              asm volatile("st.shared.u32 [%0], %1;" ::"r"(sb + OFF_BIAS + l * 512 + (lane >> 2) * 64 + i * 16 + (lane & 3) * 4),
                           "r"(pk) : "memory");
            }
          }
#pragma unroll
          for (int i = 0; i < 15; i++) {
            const uint32_t one = (lane >> 3) == (lane & 3) ? 0x3f80u << ((lane & 4) * 4) : 0u;
            asm volatile("st.shared.u32 [%0], %1;" ::"r"(sb + OFF_UNIT + i * 128 + lane * 4), "r"(i == 7 ? one : 0u) : "memory");
          }
          fence_async_smem();
          mbar_arrive(sb + BAR_BIAS);
        }
        const __nv_bfloat16* wslice = wptr + bid * 8192;
        cluster_wait();
        prefetch_1d_e(wslice + kDim * kDim, 16384);
        uint32_t nx = 0;
#pragma unroll 1
        for (int rd = 0; rd < kRounds; rd++) {
#pragma unroll 1
          for (int l = 1; l < kLayers; l++) {
            publish(nx, nx + 1 == kRounds * (kLayers - 1) ? kEpoch : nx + 1);
            nx++;
            if (l < kLayers - 1) {
              if (rd == 0) prefetch_1d_e(wslice + (l + 1) * kDim * kDim, 16384);
            } else if (rd + 1 < kRounds) {
              const int nrow = ((rd + 1) * kGroups + grp) * 128;
#pragma unroll 1
              for (int i = 0; i < 8; i++) {
                prefetch_2d_e(&mx64, j * 256 + (i >> 1) * 64, nrow + (i & 1) * 64);
                __nanosleep(300);
              }
              if ((rd + 1) * kLayers == short_t) {
                poll_flag(g_flags + (4 * kGroups + j) * 32, base + job_of_group(grp) + 1);
                fence_async_global();
                constexpr uint32_t order = 0x76325140;
#pragma unroll 1
                for (int i = NP; i < 8; i++)
                  prefetch_2d_e(&mp, j * 256 + ((order >> (i * 4)) & 3) * 64, nrow + ((order >> (i * 4)) & 4) * 16);
#pragma unroll 1
                for (int i = 0; i < 8; i++) {
                  if (i >= NP) mbar_wait(sb + BAR_PFREE + (i - NP) * 8, 0);
                  PROF(776 + i);
                  expect_load_2d_e<true>(sb + OFF_P + (i % NP) * A_SLOT, &mp, sb + BAR_PFULL + i * 8,
                                         j * 256 + ((order >> (i * 4)) & 3) * 64, nrow + ((order >> (i * 4)) & 4) * 16);
                }
              }
            }
          }
        }
#pragma unroll 1
        for (int w = 0; w < 2; w++) mbar_wait(sb + BAR_PUB + w * 8, nx & 1);
      }
    }
    if (warp == (helper ? 3 : 2) && (tid & 31) == 0) PROF_ENDS(1002);
    if (warp == 2) PROF_DUMP();
  } else {
    cluster_arrive_relaxed();
    asm volatile("setmaxnreg.inc.sync.aligned.u32 232;");
    PROF_ST(32);
    const int lane = tid & 31;
    const int wtid = tid & 127;
    const uint32_t abase = sb + OFF_A + wg * NA * A_SLOT;
    const uint32_t afull = sb + BAR_AFULL + wg * NA * 8;
    const uint32_t rel = map_cta(sb + (wtid == 64 ? BAR_BEMPTY : BAR_AEMPTY + wg * 8 - 8), wtid == 32 ? (rank ^ 1) : rank);
    const bool rel_b = wtid == 64;
    const bool rel_ab = (wtid & 31) == 0 && wtid < 96;
    const uint32_t frag0 = __shfl_sync(0xffffffffu, abase + ((wtid >> 5) * 16 + ((lane >> 3) & 1) * 8 + (lane & 7)) * 128 +
                                                        (((lane >> 4) ^ (lane & 7)) << 4), lane);
    const uint64_t adesc0 = desc(((abase & 0x3FFFF) >> 4) | DESC_A_LBO);
    const uint64_t bdesc0 = desc((((sb + OFF_B) & 0x3FFFF) >> 4) | DESC_B_LBO);

    const uint64_t zero = gridDim.y - 1;
    uint64_t adesc_q = adesc0 + zero, bdesc_q = bdesc0 + zero;

    float acc[128];
    uint32_t xr[64];
#pragma unroll
    for (int i = 0; i < 128; i++) acc[i] = kOffset;
#pragma unroll
    for (int i = 0; i < 64; i++) xr[i] = 0;
    int l = 0;
    bool hold = false;
    bool swap = false;
    bool brief = helper;
    int capture_q = helper ? -1 : j;

    auto release = [&](int i, bool with_a) {
      mbar_arrive_mapped_if(rel + i * 8, (i & 1) ? with_a : rel_b);
    };
    auto chunk_staged = [&](int c) {
      __syncwarp();
      arrive_e(sb + BAR_STAGED + (wg * NA + c) * 8);
    };
    auto capture_slot = [&](int p) {
#pragma unroll
      for (int g = 0; g < 4; g++) ldsm4(&xr[(p * 4 + g) * 4], (frag0 ^ (g * 32)) + p * A_SLOT);
    };
    auto swap_half = [&](int p, int half) {
#pragma unroll
      for (int g = half * 2; g < half * 2 + 2; g++) {
        const uint32_t addr = (frag0 ^ (g * 32)) + p * A_SLOT;
        uint32_t n[4];
        ldsm4(n, addr);
        stsm4(addr, &xr[(p * 4 + g) * 4]);
#pragma unroll
        for (int i = 0; i < 4; i++) xr[(p * 4 + g) * 4 + i] = n[i];
      }
      if (half) chunk_staged(p);
    };
    auto chunk_of = [&](int c) { return wg ? (0x7631 >> (c * 4)) & 7 : (0x5420 >> (c * 4)) & 7; };
    auto add_partial = [&](int c) __attribute__((always_inline)) {
      const int n = chunk_of(c);
      const int slot = wg ? (0x1001 >> (c * 4)) & 3 : (0x2120 >> (c * 4)) & 3;
      PROF(768 + wg * 16 + c * 2);
      mbar_spin(sb + BAR_PFULL + n * 8, 0);
      PROF(768 + wg * 16 + c * 2 + 1);
      wg_fence();
      wgmma_n256(acc, ((uint64_t)(128 >> 4) << 32) | ((128 >> 4) << 16) | (((sb + OFF_UNIT + (6 - 2 * c) * 128) & 0x3FFFF) >> 4),
                 ((uint64_t)(256 >> 4) << 32) | ((128 >> 4) << 16) | (((sb + OFF_P + slot * A_SLOT) & 0x3FFFF) >> 4));
    };
    auto issue = [&](int i, int q, int t, bool wait_b) __attribute__((always_inline)) {
      if (!(i & 1)) mbar_spin(afull + (i >> 1) * 8, q & 1);
      if (wait_b) mbar_spin(sb + (q ? BAR_BFULL : BAR_BFULL0) + i * 8, (q ? q ^ t ^ 1 : t) & 1);
      const uint64_t adesc = adesc_q + ((i >> 1) * (A_SLOT >> 4) + (i & 1) * 4);
      const uint64_t bdesc = bdesc_q + i * (B_SLOT >> 4);
      wg_fence();
      wgmma_n256(acc, adesc, bdesc);
      wgmma_n256(acc, adesc + 2, bdesc + 128);
      wg_commit();
      if (i == NB - 1) { adesc_q += zero; bdesc_q += zero; }
    };
    auto retire = [&](int i, bool with_a) {
      wg_wait<2>();
      release((i + 6) & 7, with_a);
    };
    auto k_loop = [&](auto first, int t) __attribute__((always_inline)) {
      constexpr bool FIRST = decltype(first)::value;
      const bool inject = FIRST && brief && !helper;
      const uint32_t up = moves_up(t) ? B_SLOT >> 4 : 0;
      auto extras = [&](int q, int i, bool swap_now) __attribute__((always_inline)) {
        if (!FIRST) return;
        if (swap_now) swap_half(((i + 5) >> 1) & 3, (i + 1) & 1);
        if (!(i & 1) && q == capture_q) capture_slot(i >> 1);
      };
      auto free_partial = [&](int c) {
        if (FIRST) mbar_arrive_if(sb + BAR_PFREE + chunk_of(c) * 8, inject && rel_b);
      };
      extras(0, 0, false);
#pragma unroll
      for (int i = 1; i < 8; i++) {
        if (!(i & 1)) PROF(t * 32 + wg * 16 + 8 + (i >> 1));
        if ((i == 1 || i == 7) && inject) add_partial(i >> 2);
        issue(i, 0, t, true);
        if (i >= 2) retire(i, rel_ab);
        if (i == 3) free_partial(0);
        extras(0, i, i >= 3 && swap);
      }
      PROF(t * 32 + wg * 16 + 1);
      if (!FIRST || !brief) {
#pragma unroll 1
        for (int q = 1; q < 3; q++) {
#pragma unroll
          for (int i = 0; i < 8; i++) {
            issue(i, q | 4, t, true);
            if (i == 0) PROF(t * 32 + wg * 16 + 3 + q);
            retire(i, rel_ab);
            extras(q, i, i < 3 && swap);
          }
          if (FIRST) swap = false;
          if (q == 1) bdesc_q += up;
        }
      }
      const bool rel_last = rel_b | (hold & rel_ab);
      auto with_a = [&](int slot) { return slot == 7 ? rel_ab : rel_last; };
      constexpr int JOIN = DRAIN + 2;
      constexpr int INJ = JOIN < 3 ? 3 : JOIN;
#pragma unroll
      for (int i = 0; i < DRAIN; i++) {
        issue(i, 3, t, true);
        retire(i, with_a((i + 6) & 7));
        if (i == 1) free_partial(1);
        extras(3, i, i < 3 && swap);
      }
      if (wg == 1) {
        wg_wait<1>();
        release((DRAIN + 6) & 7, with_a((DRAIN + 6) & 7));
        wg_wait<0>();
        release((DRAIN + 7) & 7, with_a((DRAIN + 7) & 7));
        if (DRAIN < 2) free_partial(1);
        PROF(t * 32 + wg * 16 + 12);
#pragma unroll
        for (int i = DRAIN; i < 3; i++) extras(-2, i, swap);
        mbar_spin(sb + BAR_ORDER, t & 1);
        PROF(t * 32 + wg * 16 + 6);
#pragma unroll
        for (int i = DRAIN; i < JOIN; i++) {
          issue(i, 3, t, true);
          extras(3, i, false);
        }
      } else {
        PROF(t * 32 + wg * 16 + 6);
#pragma unroll
        for (int i = DRAIN; i < JOIN; i++) {
          issue(i, 3, t, true);
          retire(i, with_a((i + 6) & 7));
          if (i == 1) free_partial(1);
          extras(3, i, i < 3 && swap);
        }
      }
#pragma unroll
      for (int i = JOIN; i < 8; i++) {
        if ((i == INJ || i == 7) && inject) add_partial(i == INJ ? 2 : 3);
        issue(i, 3, t, true);
        if (i == 7) mbar_arrive_if(sb + BAR_ORDER, rel_b & (wg == 0));
        retire(i, rel_last);
        if (i == INJ + 2) free_partial(2);
        extras(3, i, false);
      }
      bdesc_q -= up;
    };

    auto epilogue = [&](auto kind, int t, bool more) __attribute__((always_inline)) {
      constexpr int KIND = decltype(kind)::value;
      constexpr int PRE = KIND == 0 ? BPRE : (KIND == 1 ? HPRE : 0);
      if (KIND != 1 && t == 0) mbar_spin(sb + BAR_BIAS, 0);
      const uint32_t bl = sb + OFF_BIAS + (KIND == 1 ? kLayers - 1 : l) * 512 + ((frag0 >> 3) & 0x30);
      uint32_t bq[8][4];
      auto load_bias = [&](int U) {
        asm volatile("ld.shared.v4.u32 {%0, %1, %2, %3}, [%4];"
                     : "=r"(bq[U][0]), "=r"(bq[U][1]), "=r"(bq[U][2]), "=r"(bq[U][3]) : "r"(bl + U * 64));
      };
#pragma unroll
      for (int U = 0; U < PRE; U++) load_bias(U);
      wg_wait<1>();
      release(6, false);
      if (more) mbar_spin(sb + BAR_BFULL0, (t + 1) & 1);
      wg_wait<0>();
#pragma unroll
      for (int i = 0; i < 128; i++) asm volatile("" : "+f"(acc[i]) :: "memory");
      release(7, KIND == 0 ? rel_b : (KIND == 1 ? rel_ab : rel_b | (more & rel_ab)));
      PROF(t * 32 + wg * 16 + 2);
      if (t == 0) PROF_ST(30 + wg);

      auto pack = [&](int i, float off) {
        uint32_t v;
        asm("cvt.rn.bf16x2.f32 %0, %1, %2;" : "=r"(v) : "f"(acc[i * 2 + 1] - off), "f"(acc[i * 2] - off));
        return v;
      };
      auto cross = [&](int T, int i, float off) {
        uint32_t s2 = pack(T * 4 + i, off), o;
        asm("add.rn.bf16x2 %0, %1, %2;" : "=r"(s2) : "r"(s2), "r"(bq[T >> 1][(T & 1) * 2 + (i >> 1)]));
        asm("fma.rn.bf16x2 %0, %1, %2, %1;" : "=r"(o) : "r"(xr[T * 4 + i]), "r"(s2));
        return o;
      };
      auto reset = [&](int T) {
#pragma unroll
        for (int i = T * 8; i < T * 8 + 8; i += 4)
          asm volatile("ld.volatile.shared.v4.f32 {%0, %1, %2, %3}, [%4];"
                       : "+f"(acc[i]), "+f"(acc[i + 1]), "+f"(acc[i + 2]), "+f"(acc[i + 3]) : "r"(sb + OFF_INIT));
      };
      auto offset_for = [&](int T) { return T >= LAG ? acc[(T - LAG) * 8 + 7] : kOffset; };
      if (KIND == 2) {
        uint32_t id;
        asm volatile("mov.u32 %0, %%tid.x;" : "=r"(id));
        __nv_bfloat16* dst = optr + (size_t)(job_row(t) + wg * 64) * kDim + j * 256 + (id & 127) * 2;
        uint64_t pol;
        asm volatile("createpolicy.fractional.L2::evict_first.b64 %0, 1.0;" : "=l"(pol));
#pragma unroll
        for (int T = 0; T < 16; T++) {
#pragma unroll
          for (int i = 0; i < 4; i++)
            asm volatile("st.global.L2::cache_hint.b32 [%0], %1, %2;"
                         ::"l"(dst + (T * 4 + (i ^ 1)) * kDim), "r"(pack(T * 4 + i, offset_for(T))), "l"(pol) : "memory");
          reset(T);
        }
        asm volatile("bar.sync %0, 128;" ::"r"(wg + 1) : "memory");
        mbar_arrive_if(sb + BAR_PUB + wg * 8, rel_b);
      } else if (KIND == 1) {
#pragma unroll
        for (int T = 0; T < 16; T++) {
#pragma unroll
          for (int i = 0; i < 4; i++) xr[T * 4 + i] = cross(T, i, offset_for(T));
          if ((T & 1) && (T >> 1) + PRE < 8) load_bias((T >> 1) + PRE);
          reset(T);
        }
      } else {
#pragma unroll
        for (int T = 0; T < 16; T++) {
          uint32_t o[4];
#pragma unroll
          for (int i = 0; i < 4; i++) o[i] = cross(T, i, kOffset);
          stsm4((frag0 ^ ((T & 3) * 32)) + (T >> 2) * A_SLOT, o);
          if ((T & 3) == 3) chunk_staged(T >> 2);
          if ((T & 1) && (T >> 1) + PRE < 8) load_bias((T >> 1) + PRE);
        }
        PROF(t * 32 + wg * 16 + 7);
      }
      PROF(t * 32 + wg * 16 + 3);
    };

    PROF_ST(8);
    cluster_wait();
    PROF_ST(9);
    mbar_spin(sb + BAR_BFULL0, 0);
    PROF_ST(10);
    int t = 0;
#pragma unroll 1
    while (true) {
      if (t > 0) {
        if (helper) {
          epilogue(Int<2>(), t - 1, t < kJobs);
          if (t == kJobs) break;
        } else {
          epilogue(Int<1>(), t - 1, true);
        }
      }
      issue(0, 0, 0, false);
      if (t == 0) PROF_ST(11);
      l = 0;
      swap = t > 0 && !helper;
      brief = helper || t == short_t;
      hold = helper && t + 1 < kJobs;
      capture_q = (t > 0 || helper) ? -1 : j;
      PROF(t * 32 + wg * 16 + 0);
      k_loop(Flag<true>(), t);
      t++;
      if (helper) continue;
#pragma unroll 1
      do {
        epilogue(Int<0>(), t - 1, t < kTiles);
        if (t == kTiles) asm volatile("exit;");
        issue(0, 0, 0, false);
        l++;
        hold = l == kLayers - 1 && t + 1 < kTiles;
        PROF(t * 32 + wg * 16 + 0);
        k_loop(Flag<false>(), t);
        t++;
      } while (!hold);
    }
  }
}

__global__ void __launch_bounds__(256) dcn_fallback(const __nv_bfloat16* __restrict__ x0, const __nv_bfloat16* __restrict__ w,
                                                    const __nv_bfloat16* __restrict__ b, __nv_bfloat16* __restrict__ out) {
  __shared__ float xs[8][kDim];
  const size_t r0 = (size_t)blockIdx.x * 8;
  for (int i = threadIdx.x; i < 8 * kDim; i += 256) xs[i / kDim][i % kDim] = __bfloat162float(x0[r0 * kDim + i]);
  __syncthreads();
  for (int l = 0; l < kLayers; l++) {
    float a[4][8] = {};
    for (int k = 0; k < kDim; k++) {
#pragma unroll
      for (int c = 0; c < 4; c++) {
        const float wv = __bfloat162float(w[((size_t)l * kDim + k) * kDim + c * 256 + threadIdx.x]);
#pragma unroll
        for (int r = 0; r < 8; r++) a[c][r] += xs[r][k] * wv;
      }
    }
    __syncthreads();
#pragma unroll
    for (int c = 0; c < 4; c++) {
      const int n = c * 256 + threadIdx.x;
#pragma unroll
      for (int r = 0; r < 8; r++) {
        const float v = __bfloat162float(x0[(r0 + r) * kDim + n]) * (a[c][r] + __bfloat162float(b[l * kDim + n])) + xs[r][n];
        xs[r][n] = __bfloat162float(__float2bfloat16(v));
      }
    }
    __syncthreads();
  }
  for (int i = threadIdx.x; i < 8 * kDim; i += 256) out[r0 * kDim + i] = __float2bfloat16(xs[i / kDim][i % kDim]);
}

typedef CUresult (*EncodeFn)(CUtensorMap*, CUtensorMapDataType, cuuint32_t, void*, const cuuint64_t*, const cuuint64_t*,
                             const cuuint32_t*, const cuuint32_t*, CUtensorMapInterleave, CUtensorMapSwizzle,
                             CUtensorMapL2promotion, CUtensorMapFloatOOBfill);

static void make_map_2d(EncodeFn enc, CUtensorMap* m, void* ptr, uint64_t rows, uint32_t box_rows,
                        CUtensorMapSwizzle swizzle = CU_TENSOR_MAP_SWIZZLE_128B) {
  cuuint64_t dims[2] = {(cuuint64_t)kDim, rows};
  cuuint64_t strides[1] = {kDim * 2};
  cuuint32_t box[2] = {64, box_rows};
  cuuint32_t es[2] = {1, 1};
  enc(m, CU_TENSOR_MAP_DATA_TYPE_BFLOAT16, 2, ptr, dims, strides, box, es, CU_TENSOR_MAP_INTERLEAVE_NONE,
      swizzle, CU_TENSOR_MAP_L2_PROMOTION_L2_128B, CU_TENSOR_MAP_FLOAT_OOB_FILL_NONE);
}

}

extern "C" void kernel_launch(void* const* d_in, const int* in_sizes, int n_in, void* d_out, int out_size) {
  using namespace dcn;
  (void)in_sizes; (void)n_in; (void)out_size;
  void* fn = nullptr;
  cudaDriverEntryPointQueryResult qr;
  cudaGetDriverEntryPoint("cuTensorMapEncodeTiled", &fn, cudaEnableDefault, &qr);
  EncodeFn enc = (EncodeFn)fn;
  CUtensorMap mx64, mx32, mo64, mo32, mw, mp;
  make_map_2d(enc, &mx64, d_in[0], kRows, 64);
  make_map_2d(enc, &mx32, d_in[0], kRows, 32);
  make_map_2d(enc, &mo64, d_out, kRows, 64);
  make_map_2d(enc, &mo32, d_out, kRows, 32);
  make_map_2d(enc, &mp, d_out, kRows, 64, CU_TENSOR_MAP_SWIZZLE_NONE);
  {
    cuuint64_t dims[3] = {64, (cuuint64_t)kLayers * kDim, kDim / 64};
    cuuint64_t strides[2] = {kDim * 2, 128};
    cuuint32_t box[3] = {64, 32, 4};
    cuuint32_t es[3] = {1, 1, 1};
    enc(&mw, CU_TENSOR_MAP_DATA_TYPE_BFLOAT16, 3, d_in[1], dims, strides, box, es, CU_TENSOR_MAP_INTERLEAVE_NONE,
        CU_TENSOR_MAP_SWIZZLE_128B, CU_TENSOR_MAP_L2_PROMOTION_L2_128B, CU_TENSOR_MAP_FLOAT_OOB_FILL_NONE);
  }
  const __nv_bfloat16* x0 = (const __nv_bfloat16*)d_in[0];
  const __nv_bfloat16* w = (const __nv_bfloat16*)d_in[1];
  const __nv_bfloat16* b = (const __nv_bfloat16*)d_in[2];
  __nv_bfloat16* out = (__nv_bfloat16*)d_out;
  constexpr int smem = SMEM_BYTES + PROF_SMEM;
  cudaFuncSetAttribute(dcn_kernel, cudaFuncAttributeMaxDynamicSharedMemorySize, smem);

  cudaLaunchConfig_t cfg = {};
  cfg.gridDim = dim3(4 * kGroups + 4);
  cfg.blockDim = dim3(384);
  cfg.dynamicSmemBytes = smem;
  cudaLaunchAttribute attr;
  attr.id = cudaLaunchAttributeClusterDimension;
  attr.val.clusterDim.x = 2;
  attr.val.clusterDim.y = 1;
  attr.val.clusterDim.z = 1;
  cfg.attrs = &attr;
  cfg.numAttrs = 1;
  int clusters = 0;
  cudaOccupancyMaxActiveClusters(&clusters, dcn_kernel, &cfg);
  if (clusters >= 2 * kGroups) {
    const int grid = 4 * kGroups + (clusters >= 2 * kGroups + 2 ? 4 : 0);
    dcn_kernel<<<grid, 384, smem>>>(x0, w, b, out, mx64, mx32, mo64, mo32, mw, mp);
  } else {
    dcn_fallback<<<kRows / 8, 256>>>(x0, w, b, out);
  }
}
```

```cpp
#include <cuda_runtime.h>
#include <cuda.h>
#include <cuda_bf16.h>
#include <stdint.h>

namespace dcn {

__device__ __forceinline__ void wgmma_n256(float (&d)[128], uint64_t da, uint64_t db) {
  asm volatile("wgmma.mma_async.sync.aligned.m64n256k16.f32.bf16.bf16 "
    "{%0, %1, %2, %3, %4, %5, %6, %7, %8, %9, %10, %11, %12, %13, %14, %15, %16, %17, %18, %19, %20, %21, %22, %23, %24, %25, %26, %27, %28, %29, %30, %31, %32, %33, %34, %35, %36, %37, %38, %39, %40, %41, %42, %43, %44, %45, %46, %47, %48, %49, %50, %51, %52, %53, %54, %55, %56, %57, %58, %59, %60, %61, %62, %63, %64, %65, %66, %67, %68, %69, %70, %71, %72, %73, %74, %75, %76, %77, %78, %79, %80, %81, %82, %83, %84, %85, %86, %87, %88, %89, %90, %91, %92, %93, %94, %95, %96, %97, %98, %99, %100, %101, %102, %103, %104, %105, %106, %107, %108, %109, %110, %111, %112, %113, %114, %115, %116, %117, %118, %119, %120, %121, %122, %123, %124, %125, %126, %127}, "
    "%128, %129, 1, 1, 1, 0, 1;\n"
    : "+f"(d[0]), "+f"(d[1]), "+f"(d[2]), "+f"(d[3]), "+f"(d[4]), "+f"(d[5]), "+f"(d[6]), "+f"(d[7]), "+f"(d[8]), "+f"(d[9]), "+f"(d[10]), "+f"(d[11]), "+f"(d[12]), "+f"(d[13]), "+f"(d[14]), "+f"(d[15]), "+f"(d[16]), "+f"(d[17]), "+f"(d[18]), "+f"(d[19]), "+f"(d[20]), "+f"(d[21]), "+f"(d[22]), "+f"(d[23]), "+f"(d[24]), "+f"(d[25]), "+f"(d[26]), "+f"(d[27]), "+f"(d[28]), "+f"(d[29]), "+f"(d[30]), "+f"(d[31]), "+f"(d[32]), "+f"(d[33]), "+f"(d[34]), "+f"(d[35]), "+f"(d[36]), "+f"(d[37]), "+f"(d[38]), "+f"(d[39]), "+f"(d[40]), "+f"(d[41]), "+f"(d[42]), "+f"(d[43]), "+f"(d[44]), "+f"(d[45]), "+f"(d[46]), "+f"(d[47]), "+f"(d[48]), "+f"(d[49]), "+f"(d[50]), "+f"(d[51]), "+f"(d[52]), "+f"(d[53]), "+f"(d[54]), "+f"(d[55]), "+f"(d[56]), "+f"(d[57]), "+f"(d[58]), "+f"(d[59]), "+f"(d[60]), "+f"(d[61]), "+f"(d[62]), "+f"(d[63]), "+f"(d[64]), "+f"(d[65]), "+f"(d[66]), "+f"(d[67]), "+f"(d[68]), "+f"(d[69]), "+f"(d[70]), "+f"(d[71]), "+f"(d[72]), "+f"(d[73]), "+f"(d[74]), "+f"(d[75]), "+f"(d[76]), "+f"(d[77]), "+f"(d[78]), "+f"(d[79]), "+f"(d[80]), "+f"(d[81]), "+f"(d[82]), "+f"(d[83]), "+f"(d[84]), "+f"(d[85]), "+f"(d[86]), "+f"(d[87]), "+f"(d[88]), "+f"(d[89]), "+f"(d[90]), "+f"(d[91]), "+f"(d[92]), "+f"(d[93]), "+f"(d[94]), "+f"(d[95]), "+f"(d[96]), "+f"(d[97]), "+f"(d[98]), "+f"(d[99]), "+f"(d[100]), "+f"(d[101]), "+f"(d[102]), "+f"(d[103]), "+f"(d[104]), "+f"(d[105]), "+f"(d[106]), "+f"(d[107]), "+f"(d[108]), "+f"(d[109]), "+f"(d[110]), "+f"(d[111]), "+f"(d[112]), "+f"(d[113]), "+f"(d[114]), "+f"(d[115]), "+f"(d[116]), "+f"(d[117]), "+f"(d[118]), "+f"(d[119]), "+f"(d[120]), "+f"(d[121]), "+f"(d[122]), "+f"(d[123]), "+f"(d[124]), "+f"(d[125]), "+f"(d[126]), "+f"(d[127])
    : "l"(da), "l"(db));
}

constexpr int kDim = 1024;
constexpr int kRows = 16384;
constexpr int kLayers = 6;
constexpr int kGroups = 32;
constexpr int kRounds = kRows / 128 / kGroups;
constexpr int kTiles = kRounds * kLayers;

constexpr int kJobs = kGroups;
constexpr int kEpoch = 32;
constexpr int NA = 4;
constexpr int NB = 8;
constexpr float kOffset = 85.333336f;
constexpr float kTrunc = 64 * 0.375f / 131072;
constexpr int DRAIN = 1;
constexpr int LAG = 3;
constexpr int BPRE = 5;
constexpr int HPRE = 6;
constexpr int NF = 2;
constexpr int A_SLOT = 8192;
constexpr int B_SLOT = 16384;
constexpr int OFF_B = 0;
constexpr int NP = 3;
constexpr int OFF_P = OFF_B + NB * B_SLOT;
constexpr int OFF_A = OFF_P + NP * A_SLOT;
constexpr int OFF_UNIT = OFF_A + 2 * NA * A_SLOT;
constexpr int OFF_BIAS = OFF_UNIT + 2048;
constexpr int OFF_INIT = OFF_BIAS + kLayers * 256 * 2;
constexpr int OFF_BAR = OFF_INIT + 16;
constexpr int BAR_BFULL = OFF_BAR;
constexpr int BAR_BFULL0 = BAR_BFULL + NB * 8;
constexpr int BAR_BEMPTY = BAR_BFULL0 + NB * 8;
constexpr int BAR_AFULL = BAR_BEMPTY + NB * 8;
constexpr int BAR_AEMPTY = BAR_AFULL + 2 * NA * 8;
constexpr int BAR_XREADY = BAR_AEMPTY + 2 * NA * 8;
constexpr int BAR_PUB = BAR_XREADY + 16;
constexpr int BAR_PFULL = BAR_PUB + 16;
constexpr int BAR_PFREE = BAR_PFULL + 8 * 8;
constexpr int BAR_STAGED = BAR_PFREE + 8 * 8;
constexpr int BAR_ORDER = BAR_STAGED + 2 * NA * 8;
constexpr int BAR_BIAS = BAR_ORDER + 8;
constexpr int SMEM_BYTES = BAR_BIAS + 8;
static_assert(SMEM_BYTES <= 232448, "shared memory budget");

constexpr int kFlagSet = 4 * (kGroups + 1) * 32;
__device__ unsigned int g_flags[3 * kFlagSet];

__device__ __forceinline__ uint32_t smem_u32(const void* p) { return (uint32_t)__cvta_generic_to_shared(p); }
__device__ __forceinline__ void mbar_init(uint32_t bar, int cnt) {
  asm volatile("mbarrier.init.shared::cta.b64 [%0], %1;" ::"r"(bar), "r"(cnt) : "memory");
}
__device__ __forceinline__ void mbar_arrive(uint32_t bar) {
  asm volatile("mbarrier.arrive.shared::cta.b64 _, [%0];" ::"r"(bar) : "memory");
}
__device__ __forceinline__ uint32_t map_cta(uint32_t addr, uint32_t cta) {
  uint32_t r;
  asm volatile("mapa.shared::cluster.u32 %0, %1, %2;" : "=r"(r) : "r"(addr), "r"(cta));
  return r;
}
__device__ __forceinline__ void mbar_arrive_mapped_if(uint32_t cluster_addr, bool pred) {
  asm volatile("{\n.reg .pred p;\nsetp.ne.u32 p, %1, 0;\n@p mbarrier.arrive.shared::cluster.b64 _, [%0];\n}"
               ::"r"(cluster_addr), "r"((uint32_t)pred) : "memory");
}
__device__ __forceinline__ void mbar_arrive_if(uint32_t bar, bool pred) {
  asm volatile("{\n.reg .pred p;\nsetp.ne.u32 p, %1, 0;\n@p mbarrier.arrive.shared::cta.b64 _, [%0];\n}"
               ::"r"(bar), "r"((uint32_t)pred) : "memory");
}
__device__ __forceinline__ void mbar_wait(uint32_t bar, uint32_t parity) {
  asm volatile(
      "{\n.reg .pred p;\n.reg .u32 c;\n"
      "mbarrier.try_wait.parity.shared::cta.b64 p, [%0], %1;\n"
      "@p bra DONE;\n"
      "mov.u32 c, 0;\n"
      "LOOP:\n"
      "mbarrier.try_wait.parity.shared::cta.b64 p, [%0], %1;\n"
      "@p bra DONE;\n"
      "add.u32 c, c, 1;\n"
      "setp.lt.u32 p, c, 1048576;\n"
      "@p bra LOOP;\n"
      "trap;\n"
      "DONE:\n}"
      ::"r"(bar), "r"(parity) : "memory");
}
__device__ __forceinline__ void mbar_spin(uint32_t bar, uint32_t parity) {
  asm volatile(
      "{\n.reg .pred p;\n"
      "LOOP:\n"
      "mbarrier.try_wait.parity.shared::cta.b64 p, [%0], %1;\n"
      "@!p bra LOOP;\n}"
      ::"r"(bar), "r"(parity) : "memory");
}
#define ELECT_BEGIN "{\n.reg .pred e;\nelect.sync _|e, 0xffffffff;\n"
template <bool STREAM> __device__ __forceinline__ void expect_load_2d_e(uint32_t dst, const CUtensorMap* m, uint32_t bar, int c0, int c1) {
  if (STREAM) {
    asm volatile(ELECT_BEGIN ".reg .b64 pol;\ncreatepolicy.fractional.L2::evict_first.b64 pol, 1.0;\n"
                 "@e mbarrier.arrive.expect_tx.shared::cta.b64 _, [%2], 8192;\n"
                 "@e cp.async.bulk.tensor.2d.shared::cluster.global.mbarrier::complete_tx::bytes.L2::cache_hint [%0], [%1, {%3, %4}], [%2], pol;\n}"
                 ::"r"(dst), "l"(m), "r"(bar), "r"(c0), "r"(c1) : "memory");
  } else {
    asm volatile(ELECT_BEGIN
                 "@e mbarrier.arrive.expect_tx.shared::cta.b64 _, [%2], 8192;\n"
                 "@e cp.async.bulk.tensor.2d.shared::cluster.global.mbarrier::complete_tx::bytes [%0], [%1, {%3, %4}], [%2];\n}"
                 ::"r"(dst), "l"(m), "r"(bar), "r"(c0), "r"(c1) : "memory");
  }
}
__device__ __forceinline__ void expect_load_2d_mc_e(uint32_t dst, const CUtensorMap* m, uint32_t bar, int c0, int c1) {
  asm volatile(ELECT_BEGIN ".reg .b64 pol;\ncreatepolicy.fractional.L2::evict_first.b64 pol, 1.0;\n"
               "@e mbarrier.arrive.expect_tx.shared::cta.b64 _, [%2], 8192;\n"
               "@e cp.async.bulk.tensor.2d.shared::cluster.global.mbarrier::complete_tx::bytes.multicast::cluster.L2::cache_hint [%0], [%1, {%3, %4}], [%2], %5, pol;\n}"
               ::"r"(dst), "l"(m), "r"(bar), "r"(c0), "r"(c1), "h"((uint16_t)3) : "memory");
}
__device__ __forceinline__ void expect_load_3d_e(uint32_t dst, const CUtensorMap* m, uint32_t bar, int c0, int c1, int c2) {
  asm volatile(ELECT_BEGIN
               "@e mbarrier.arrive.expect_tx.shared::cta.b64 _, [%2], 16384;\n"
               "@e cp.async.bulk.tensor.3d.shared::cluster.global.mbarrier::complete_tx::bytes [%0], [%1, {%3, %4, %5}], [%2];\n}"
               ::"r"(dst), "l"(m), "r"(bar), "r"(c0), "r"(c1), "r"(c2) : "memory");
}
template <bool STREAM> __device__ __forceinline__ void store_2d_e(const CUtensorMap* m, uint32_t src, int c0, int c1) {
  if (STREAM) {
    asm volatile(ELECT_BEGIN ".reg .b64 pol;\ncreatepolicy.fractional.L2::evict_first.b64 pol, 1.0;\n"
                 "@e cp.async.bulk.tensor.2d.global.shared::cta.bulk_group.L2::cache_hint [%0, {%2, %3}], [%1], pol;\n}"
                 ::"l"(m), "r"(src), "r"(c0), "r"(c1) : "memory");
  } else {
    asm volatile(ELECT_BEGIN
                 "@e cp.async.bulk.tensor.2d.global.shared::cta.bulk_group [%0, {%2, %3}], [%1];\n}"
                 ::"l"(m), "r"(src), "r"(c0), "r"(c1) : "memory");
  }
}
__device__ __forceinline__ void prefetch_2d_e(const CUtensorMap* m, int c0, int c1) {
  asm volatile(ELECT_BEGIN
               "@e cp.async.bulk.prefetch.tensor.2d.L2.global [%0, {%1, %2}];\n}"
               ::"l"(m), "r"(c0), "r"(c1) : "memory");
}
__device__ __forceinline__ void prefetch_1d_e(const void* ptr, uint32_t bytes) {
  asm volatile(ELECT_BEGIN
               "@e cp.async.bulk.prefetch.L2.global [%0], %1;\n}"
               ::"l"(ptr), "r"(bytes) : "memory");
}
__device__ __forceinline__ void paced_load_3d_e(uint32_t dst, const CUtensorMap* m, uint32_t bar, int c0, int c1, int c2, bool pace) {
  asm volatile(ELECT_BEGIN ".reg .pred p;\nsetp.ne.u32 p, %6, 0;\n"
               "@e mbarrier.arrive.expect_tx.shared::cta.b64 _, [%2], 16384;\n"
               "@p nanosleep.u32 128;\n"
               "@e cp.async.bulk.tensor.3d.shared::cluster.global.mbarrier::complete_tx::bytes [%0], [%1, {%3, %4, %5}], [%2];\n}"
               ::"r"(dst), "l"(m), "r"(bar), "r"(c0), "r"(c1), "r"(c2), "r"((uint32_t)pace) : "memory");
}
__device__ __forceinline__ void arrive_mapped_e(uint32_t cluster_addr) {
  asm volatile(ELECT_BEGIN "@e mbarrier.arrive.shared::cluster.b64 _, [%0];\n}" ::"r"(cluster_addr) : "memory");
}
__device__ __forceinline__ void arrive_e(uint32_t bar) {
  asm volatile(ELECT_BEGIN "@e mbarrier.arrive.shared::cta.b64 _, [%0];\n}" ::"r"(bar) : "memory");
}
__device__ __forceinline__ void bulk_commit() { asm volatile("cp.async.bulk.commit_group;" ::: "memory"); }
template <int N> __device__ __forceinline__ void bulk_wait() { asm volatile("cp.async.bulk.wait_group %0;" ::"n"(N) : "memory"); }
__device__ __forceinline__ void wg_fence() { asm volatile("wgmma.fence.sync.aligned;" ::: "memory"); }
__device__ __forceinline__ void wg_commit() { asm volatile("wgmma.commit_group.sync.aligned;" ::: "memory"); }
template <int N> __device__ __forceinline__ void wg_wait() { asm volatile("wgmma.wait_group.sync.aligned %0;" ::"n"(N) : "memory"); }
__device__ __forceinline__ void fence_async_global() { asm volatile("fence.proxy.async.global;" ::: "memory"); }
__device__ __forceinline__ void st_relaxed(unsigned int* p, unsigned int v) {
  asm volatile("st.relaxed.gpu.global.u32 [%0], %1;" ::"l"(p), "r"(v) : "memory");
}
__device__ __forceinline__ void ldsm4(uint32_t* r, uint32_t addr) {
  asm volatile("ldmatrix.sync.aligned.m8n8.x4.shared.b16 {%0, %1, %2, %3}, [%4];"
               : "=r"(r[0]), "=r"(r[1]), "=r"(r[2]), "=r"(r[3]) : "r"(addr) : "memory");
}
__device__ __forceinline__ void stsm4(uint32_t addr, const uint32_t* r) {
  asm volatile("stmatrix.sync.aligned.m8n8.x4.shared.b16 [%0], {%1, %2, %3, %4};"
               ::"r"(addr), "r"(r[0]), "r"(r[1]), "r"(r[2]), "r"(r[3]) : "memory");
}
template <bool V> struct Flag { static constexpr bool value = V; };
template <int V> struct Int { static constexpr int value = V; };
__device__ __forceinline__ void fence_async_smem() { asm volatile("fence.proxy.async.shared::cta;" ::: "memory"); }
__device__ __forceinline__ void cluster_arrive_relaxed() { asm volatile("barrier.cluster.arrive.relaxed.aligned;" ::: "memory"); }
__device__ __forceinline__ void cluster_wait() { asm volatile("barrier.cluster.wait.acquire.aligned;" ::: "memory"); }
__device__ __forceinline__ void prefetch_map(const CUtensorMap* m) {
  asm volatile("prefetch.tensormap [%0];" ::"l"(m) : "memory");
}
__device__ __forceinline__ void prefetch_map_e(const CUtensorMap* m) {
  asm volatile(ELECT_BEGIN "@e prefetch.tensormap [%0];\n}" ::"l"(m) : "memory");
}
__device__ __forceinline__ void poll_flag(const unsigned int* ptr, unsigned int target) {
  asm volatile(
      "{\n.reg .pred p;\n.reg .u32 c;\n.reg .s32 v;\n"
      "mov.u32 c, 0;\n"
      "LOOP:\n"
      "ld.acquire.gpu.global.s32 v, [%0];\n"
      "sub.s32 v, v, %1;\n"
      "setp.ge.s32 p, v, 0;\n"
      "@p bra DONE;\n"
      "add.u32 c, c, 1;\n"
      "setp.lt.u32 p, c, 1048576;\n"
      "@p bra LOOP;\n"
      "trap;\n"
      "DONE:\n}"
      ::"l"(ptr), "r"(target) : "memory");
}

constexpr uint32_t DESC_HI = (1024u >> 4) | (1u << 30);
__device__ __forceinline__ uint64_t desc(uint32_t lo) { return ((uint64_t)DESC_HI << 32) | lo; }
constexpr uint32_t DESC_A_LBO = 1u << 16;
constexpr uint32_t DESC_B_LBO = (4096u >> 4) << 16;

__device__ __forceinline__ int kgroup_col(int j, int q) {
  return q == 0 ? j : (q == 1 ? (j ^ 1) : (((j ^ 2) & ~1) + (q - 2)));
}

__device__ __forceinline__ int role_of_cluster(int c) {
  const int a = c - 4;
  const int b = c - 36, r = (b * 37) >> 8;
  const int first = (a & ~7) + (a & 3) * 2 + ((a >> 2) & 1);
  const int second = 32 + r * 8 + ((0x7531640 >> (((b - r * 7) * 4) & 31)) & 7);
  return c >= 2 * kGroups ? c : (c >= 36 ? second : (c >= 4 ? first : 34 + c * 8));
}
__device__ __forceinline__ int helped_round(int grp) { return (grp & 2) ? (grp & 3) - 1 : 3; }
__device__ __forceinline__ int job_of_group(int grp) {
  return (grp & 2) ? (grp & 1) * 8 + (grp >> 2) : 16 + (grp >> 2) * 2 + (grp & 1);
}
__device__ __forceinline__ int job_row(int n) {
  const int grp = n < 16 ? (n & 7) * 4 + 2 + (n >> 3) : ((n - 16) >> 1) * 4 + (n & 1);
  return (helped_round(grp) * kGroups + grp) * 128;
}

constexpr int PROF_SMEM = 0;
#define PROF_BOTH(idx) do {} while (0)
#define PROF_SVC(idx) do {} while (0)
#define PROF_DUMP() do {} while (0)
#define PROF(idx) do {} while (0)
#define PROF_ST(idx) do {} while (0)
#define PROF_SKEW(idx) do {} while (0)

__global__ void __cluster_dims__(2, 1, 1) __launch_bounds__(384, 1)
dcn_kernel(const __nv_bfloat16* __restrict__ xptr, const __nv_bfloat16* __restrict__ wptr,
           const __nv_bfloat16* __restrict__ bias, __nv_bfloat16* optr,
           const __grid_constant__ CUtensorMap mx64, const __grid_constant__ CUtensorMap mx32,
           const __grid_constant__ CUtensorMap mo64, const __grid_constant__ CUtensorMap mo32,
           const __grid_constant__ CUtensorMap mw, const __grid_constant__ CUtensorMap mp) {
  extern __shared__ __align__(1024) uint8_t smem_raw[];
  const uint32_t sb = smem_u32(smem_raw);
  const int tid = threadIdx.x;
  if ((tid >> 5) == 8) PROF_ST(0);
  if ((tid >> 5) == 9) PROF_BOTH(48);
  const int wid = __shfl_sync(0xffffffffu, tid >> 5, 0);
  if (wid == 0) {
    asm volatile("prefetch.global.L2 [%0];" ::"l"(wptr + ((blockIdx.x & 31) * 32 + tid) * 64));
    asm volatile("prefetch.global.L2 [%0];" ::"l"(xptr + ((blockIdx.x & 127) * 32 + tid) * kDim));
    prefetch_map_e(&mw);
    prefetch_map_e(&mx64);
    PROF_ST(29);
  }
  const int bid = role_of_cluster(blockIdx.x >> 1) * 2 + (blockIdx.x & 1);
  const int j = bid & 3;
  const int grp = bid >> 2;
  const bool helper = grp == kGroups;
  const int col0 = helper ? kgroup_col(j, 2) * 256 : 0;
  const int row0 = helper ? job_row(0) : grp * 128;
  auto first_loads = [&](int s) {
    const int col = col0 + s * 64;
    expect_load_3d_e(sb + OFF_B + 2 * s * B_SLOT, &mw, sb + BAR_BFULL0 + 2 * s * 8, 0, col, j * 4);
    expect_load_2d_e<false>(sb + OFF_A + s * A_SLOT, &mx64, sb + BAR_AFULL + s * 8, col, row0);
    expect_load_3d_e(sb + OFF_B + (2 * s + 1) * B_SLOT, &mw, sb + BAR_BFULL0 + (2 * s + 1) * 8, 0, col + 32, j * 4);
    expect_load_2d_e<false>(sb + OFF_A + (NA + s) * A_SLOT, &mx64, sb + BAR_AFULL + (NA + s) * 8, col, row0 + 64);
    PROF_ST(2 + s);
  };
  auto init_full = [&](int s) {
    mbar_init(sb + BAR_BFULL0 + 2 * s * 8, 1);
    mbar_init(sb + BAR_BFULL0 + (2 * s + 1) * 8, 1);
    mbar_init(sb + BAR_AFULL + s * 8, 1);
    mbar_init(sb + BAR_AFULL + (NA + s) * 8, 1);
  };
  if (wid == 8) {
    PROF_ST(28);
    if (tid == 256) {
      init_full(0);
      asm volatile("fence.mbarrier_init.release.cluster;" ::: "memory");
    }
    __syncwarp();
    PROF_ST(1);
    first_loads(0);
    if (tid == 256) {
#pragma unroll
      for (int s = 1; s < 4; s++) init_full(s);
      asm volatile("fence.mbarrier_init.release.cluster;" ::: "memory");
    }
    __syncwarp();
#pragma unroll
    for (int s = 1; s < NF; s++) first_loads(s);
  }
  const int wg = wid >> 2;
  const int warp = wid & 3;
  const uint32_t rank = j & 1;
  const int short_t = (gridDim.x > 4 * kGroups && !helper) ? helped_round(grp) * kLayers : -8;
  const unsigned lend = helper ? ~0u : 1u;
  auto moves_up = [&](int t) { return (unsigned)(t + 1 - short_t) > lend; };

  if (wg == 2) {
    asm volatile("setmaxnreg.dec.sync.aligned.u32 40;");
    if (tid == 288) {
      if (sb & 1023) asm volatile("trap;");
#pragma unroll
      for (int i = 0; i < NB; i++) { mbar_init(sb + BAR_BFULL + i * 8, 1); mbar_init(sb + BAR_BEMPTY + i * 8, 2); }
#pragma unroll
      for (int i = 0; i < 4; i++) mbar_init(sb + BAR_XREADY + i * 8, 1);
      mbar_init(sb + BAR_ORDER, 1);
    } else if (tid == 320) {
#pragma unroll
      for (int i = 0; i < 2 * NA; i++) { mbar_init(sb + BAR_AEMPTY + i * 8, 2); mbar_init(sb + BAR_STAGED + i * 8, 4); }
    } else if (tid == 352) {
#pragma unroll
      for (int i = 0; i < 8; i++) { mbar_init(sb + BAR_PFULL + i * 8, 1); mbar_init(sb + BAR_PFREE + i * 8, 1); }
      mbar_init(sb + BAR_BIAS, 32);
      asm volatile("st.shared.v4.f32 [%0], {%1, %1, %1, %1};" ::"r"(sb + OFF_INIT), "f"(kOffset) : "memory");
    }
    asm volatile("fence.mbarrier_init.release.cluster;" ::: "memory");
    __syncwarp();
    cluster_arrive_relaxed();
    if (warp == 0) {
      PROF_ST(6);
#pragma unroll 1
      for (int s = NF; s < 4; s++) first_loads(s);
      cluster_wait();
      PROF_ST(7);
      uint32_t par = 0;
      int l = 0;
      const int ntiles = helper ? kJobs : kTiles;
#pragma unroll 1
      for (int t = 0; t < ntiles; t++) {
        const int jo = (t == 0 && !helper) ? 0 : j;
        const int q_end = t == short_t ? 2 : 4;
#pragma unroll 1
        for (int q = (helper ? 2 : 0) + (t == 0); q < q_end; q++) {
          const int krow = l * kDim + kgroup_col(jo, q) * 256;
          const bool first = q == (helper ? 2 : 0);
          const bool up = q >= 2 && moves_up(t);
          const int shift = first ? (moves_up(t - 1) ? -1 : 0) : (up && q == 2 ? 1 : 0);
          const int paced = first ? (shift ? DRAIN + 1 : 0) : ((helper || (q == 1 && (t == short_t || t == 0))) ? 0 : NB);
          const uint32_t dst = sb + OFF_B + (up ? B_SLOT : 0);
          const uint32_t full = sb + (first ? BAR_BFULL0 : BAR_BFULL);
          if (shift > 0) mbar_spin(sb + BAR_BEMPTY, par);
#pragma unroll 1
          for (int i = 0; i < NB; i++) {
            if ((unsigned)(i + shift) < NB) mbar_spin(sb + BAR_BEMPTY + (i + shift) * 8, par);
            paced_load_3d_e(dst + i * B_SLOT, &mw, full + i * 8, 0, krow + i * 32, j * 4, i < paced);
            PROF_SKEW(t * 32 + q * 8 + i);
          }
          if (shift < 0) mbar_spin(sb + BAR_BEMPTY + (NB - 1) * 8, par);
          par ^= 1;
        }
        if (helper || ++l == kLayers) l = 0;
      }
    } else if (warp <= 2) {
      const int w = warp - 1;
      const uint32_t abase = sb + OFF_A + w * NA * A_SLOT;
      const uint32_t fullb = sb + BAR_AFULL + w * NA * 8;
      const uint32_t emptyb = sb + BAR_AEMPTY + w * 8;
      const uint32_t stagedb = sb + BAR_STAGED + w * NA * 8;
      const unsigned int base = __shfl_sync(0xffffffffu, *(volatile unsigned int*)(g_flags + bid * 32), 0);
      cluster_wait();
      uint32_t epar = 0;
      uint32_t spar = 0;
      auto refill = [&](const CUtensorMap* m, int col, int row) {
#pragma unroll 1
        for (int s = 0; s < 4; s++) {
          mbar_spin(emptyb + s * 16, epar);
          expect_load_2d_e<false>(abase + s * A_SLOT, m, fullb + s * 8, col + s * 64, row);
        }
        epar ^= 1;
      };
      auto store_refill = [&](int out_row, int col, int row, bool last_read) {
#pragma unroll 1
        for (int s = 0; s < 4; s++) {
          mbar_spin(stagedb + s * 8, spar);
          fence_async_smem();
          store_2d_e<true>(&mo64, abase + s * A_SLOT, j * 256 + s * 64, out_row);
          bulk_commit();
          bulk_wait<0>();
          __syncwarp();
          mbar_spin(emptyb + s * 16, epar);
          if (last_read) expect_load_2d_e<true>(abase + s * A_SLOT, &mx64, fullb + s * 8, col + s * 64, row);
          else expect_load_2d_e<false>(abase + s * A_SLOT, &mx64, fullb + s * 8, col + s * 64, row);
        }
        spar ^= 1;
        epar ^= 1;
      };
      auto store_tile = [&](auto stream, int out_row) {
#pragma unroll 1
        for (int c = 0; c < 4; c++) {
          mbar_spin(stagedb + c * 8, spar);
          fence_async_smem();
          arrive_e(fullb + c * 8);
          if (!decltype(stream)::value && w == 1) {
            bulk_commit();
            bulk_wait<0>();
          }
          store_2d_e<decltype(stream)::value>(&mo64, abase + c * A_SLOT, j * 256 + c * 64, out_row);
        }
        spar ^= 1;
        bulk_commit();
        bulk_wait<0>();
        __syncwarp();
      };
      auto refill_shared = [&](const CUtensorMap* m32, int col, int row) {
#pragma unroll 1
        for (int s = 0; s < 4; s++) {
          mbar_spin(emptyb + s * 16, epar);
          expect_load_2d_mc_e(abase + s * A_SLOT + rank * 4096, m32, fullb + s * 8, col + s * 64, row + rank * 32);
        }
        epar ^= 1;
      };
      if (helper) {
#pragma unroll 1
        for (int h = 1; h < 2 * kJobs; h++) refill_shared(&mx32, col0 + (h & 1) * 256, job_row(h >> 1) + w * 64);
      } else {
        const uint32_t xready_peer = map_cta(sb + BAR_XREADY + w * 8, rank ^ 1);
        const unsigned int* oflag = g_flags + (grp * 4 + kgroup_col(j, 2)) * 32;
        unsigned int* done_mine = g_flags + kFlagSet + (bid * 2 + w) * 32;
        const unsigned int* done_peer = g_flags + kFlagSet + ((bid ^ 2) * 2 + w) * 32;
        uint32_t nx = 0;
#pragma unroll 1
        for (int rd = 0; rd < kRounds; rd++) {
          const int xrow = (rd * kGroups + grp) * 128 + w * 64;
          if (rd == 0) {
            refill(&mx64, 256, xrow);
          } else {
            poll_flag(done_peer, base + nx);
            store_refill(xrow - kGroups * 128, (j ^ 1) * 256, xrow, rd * kLayers == short_t);
          }
          if (rd * kLayers != short_t) {
#pragma unroll 1
            for (int h = 0; h < 2; h++) refill_shared(&mx32, (kgroup_col(rd == 0 ? 0 : j, 2) + h) * 256, xrow);
          }
#pragma unroll 1
          for (int l = 1; l < kLayers; l++) {
            if (l > 1) poll_flag(done_peer, base + nx);
            store_tile(Flag<false>(), xrow);
            PROF_SVC((rd * kLayers + l - 1) * 2 + w);
            arrive_mapped_e(xready_peer);
            arrive_e(sb + BAR_PUB + w * 8);
            mbar_spin(sb + BAR_XREADY + w * 8, nx & 1);
            fence_async_global();
            refill(&mo64, (j ^ 1) * 256, xrow);
#pragma unroll 1
            for (int h = 0; h < 2; h++) {
              poll_flag(oflag + h * 32, base + nx + 1);
              fence_async_global();
              refill_shared(&mo32, (kgroup_col(j, 2) + h) * 256, xrow);
            }
            if (rank) {
#pragma unroll 1
              for (int s = 0; s < 4; s++) mbar_spin(fullb + s * 8, 1);
            }
            nx++;
            if ((tid & 31) == 0) st_relaxed(done_mine, base + (nx == kRounds * (kLayers - 1) ? kEpoch : nx));
            __syncwarp();
          }
          const int nrow = xrow + kGroups * 128;
          if (rd + 1 == kRounds) {
            poll_flag(done_peer, base + nx);
            store_tile(Flag<true>(), xrow);
            PROF_SVC((rd * kLayers + kLayers - 1) * 2 + w);
            arrive_e(sb + BAR_PUB + w * 8);
          } else {
            refill(&mx64, j * 256, nrow);
            PROF_SVC((rd * kLayers + kLayers - 1) * 2 + w);
          }
        }
      }
    } else {
      const int lane = tid & 31;
      unsigned int* myflag = g_flags + bid * 32;
      if (lane == 0) { prefetch_map(&mx32); prefetch_map(&mo64); prefetch_map(&mo32); }
      const unsigned int base = *(volatile unsigned int*)myflag;
      auto publish = [&](uint32_t n, uint32_t value) {
#pragma unroll 1
        for (int w = 0; w < 2; w++) mbar_wait(sb + BAR_PUB + w * 8, n & 1);
        if (lane == 0) asm volatile("st.release.gpu.global.u32 [%0], %1;" ::"l"(myflag), "r"(base + value) : "memory");
        __syncwarp();
      };
      if (helper) {
        mbar_arrive(sb + BAR_BIAS);
        cluster_wait();
#pragma unroll 1
        for (int n = 0; n < kJobs; n++) {
          if (n + 2 < kJobs) {
            const int row = job_row(n + 2);
#pragma unroll 1
            for (int i = 0; i < 8; i++) prefetch_2d_e(&mx64, col0 + rank * 256 + (i & 3) * 64, row + (i >> 2) * 64);
          }
          publish(n, n + 1);
        }
      } else {
        {
          float c[8];
#pragma unroll
          for (int i = 0; i < 8; i++) c[i] = 0.f;
#pragma unroll 1
          for (int l = 0; l < kLayers; l++) {
            const uint4 v = *reinterpret_cast<const uint4*>(bias + l * kDim + j * 256 + lane * 8);
            const uint32_t u[4] = {v.x, v.y, v.z, v.w};
#pragma unroll
            for (int i = 0; i < 4; i++) {
              c[2 * i] += __uint_as_float(u[i] << 16) + kTrunc;
              c[2 * i + 1] += __uint_as_float(u[i] & 0xffff0000u) + kTrunc;
              uint32_t pk;
              asm("cvt.rn.bf16x2.f32 %0, %1, %2;" : "=r"(pk) : "f"(c[2 * i + 1]), "f"(c[2 * i]));
              asm volatile("st.shared.u32 [%0], %1;" ::"r"(sb + OFF_BIAS + l * 512 + (lane >> 2) * 64 + i * 16 + (lane & 3) * 4),
                           "r"(pk) : "memory");
            }
          }
#pragma unroll
          for (int i = 0; i < 15; i++) {
            const uint32_t one = (lane >> 3) == (lane & 3) ? 0x3f80u << ((lane & 4) * 4) : 0u;
            asm volatile("st.shared.u32 [%0], %1;" ::"r"(sb + OFF_UNIT + i * 128 + lane * 4), "r"(i == 7 ? one : 0u) : "memory");
          }
          fence_async_smem();
          mbar_arrive(sb + BAR_BIAS);
        }
        const __nv_bfloat16* wslice = wptr + bid * 8192;
        cluster_wait();
        prefetch_1d_e(wslice + kDim * kDim, 16384);
        uint32_t nx = 0;
#pragma unroll 1
        for (int rd = 0; rd < kRounds; rd++) {
#pragma unroll 1
          for (int l = 1; l < kLayers; l++) {
            publish(nx, nx + 1 == kRounds * (kLayers - 1) ? kEpoch : nx + 1);
            nx++;
            if (l < kLayers - 1 && rd == 0) prefetch_1d_e(wslice + (l + 1) * kDim * kDim, 16384);
            if (l > 1 && rd + 1 < kRounds) {
              const int nrow = ((rd + 1) * kGroups + grp) * 128;
              prefetch_1d_e(xptr + (size_t)(nrow + j * 32 + l * 8 - 16) * kDim, 8192);
              __nanosleep(600);
              prefetch_1d_e(xptr + (size_t)(nrow + j * 32 + l * 8 - 12) * kDim, 8192);
              if (rd * kLayers + l + 1 == short_t) {
                poll_flag(g_flags + (4 * kGroups + j) * 32, base + job_of_group(grp) + 1);
                fence_async_global();
                constexpr uint32_t order = 0x76325140;
#pragma unroll 1
                for (int i = NP; i < 8; i++)
                  prefetch_2d_e(&mp, j * 256 + ((order >> (i * 4)) & 3) * 64, nrow + ((order >> (i * 4)) & 4) * 16);
#pragma unroll 1
                for (int i = 0; i < 8; i++) {
                  if (i >= NP) mbar_wait(sb + BAR_PFREE + (i - NP) * 8, 0);
                  PROF(776 + i);
                  expect_load_2d_e<true>(sb + OFF_P + (i % NP) * A_SLOT, &mp, sb + BAR_PFULL + i * 8,
                                         j * 256 + ((order >> (i * 4)) & 3) * 64, nrow + ((order >> (i * 4)) & 4) * 16);
                }
              }
            }
          }
        }
#pragma unroll 1
        for (int w = 0; w < 2; w++) mbar_wait(sb + BAR_PUB + w * 8, nx & 1);
      }
    }
    if (warp == 3) PROF_DUMP();
  } else {
    cluster_arrive_relaxed();
    asm volatile("setmaxnreg.inc.sync.aligned.u32 232;");
    PROF_ST(32);
    const int lane = tid & 31;
    const int wtid = tid & 127;
    const uint32_t abase = sb + OFF_A + wg * NA * A_SLOT;
    const uint32_t afull = sb + BAR_AFULL + wg * NA * 8;
    const uint32_t rel = map_cta(sb + (wtid == 64 ? BAR_BEMPTY : BAR_AEMPTY + wg * 8 - 8), wtid == 32 ? (rank ^ 1) : rank);
    const bool rel_b = wtid == 64;
    const bool rel_ab = (wtid & 31) == 0 && wtid < 96;
    const uint32_t frag0 = __shfl_sync(0xffffffffu, abase + ((wtid >> 5) * 16 + ((lane >> 3) & 1) * 8 + (lane & 7)) * 128 +
                                                        (((lane >> 4) ^ (lane & 7)) << 4), lane);
    const uint64_t adesc0 = desc(((abase & 0x3FFFF) >> 4) | DESC_A_LBO);
    const uint64_t bdesc0 = desc((((sb + OFF_B) & 0x3FFFF) >> 4) | DESC_B_LBO);

    const uint64_t zero = gridDim.y - 1;
    uint64_t adesc_q = adesc0 + zero, bdesc_q = bdesc0 + zero;

    float acc[128];
    uint32_t xr[64];
#pragma unroll
    for (int i = 0; i < 128; i++) acc[i] = kOffset;
#pragma unroll
    for (int i = 0; i < 64; i++) xr[i] = 0;
    int l = 0;
    bool hold = false;
    bool swap = false;
    bool brief = helper;
    int capture_q = helper ? -1 : j;

    auto release = [&](int i, bool with_a) {
      mbar_arrive_mapped_if(rel + i * 8, (i & 1) ? with_a : rel_b);
    };
    auto chunk_staged = [&](int c) {
      __syncwarp();
      arrive_e(sb + BAR_STAGED + (wg * NA + c) * 8);
    };
    auto capture_slot = [&](int p) {
#pragma unroll
      for (int g = 0; g < 4; g++) ldsm4(&xr[(p * 4 + g) * 4], (frag0 ^ (g * 32)) + p * A_SLOT);
    };
    auto swap_half = [&](int p, int half) {
#pragma unroll
      for (int g = half * 2; g < half * 2 + 2; g++) {
        const uint32_t addr = (frag0 ^ (g * 32)) + p * A_SLOT;
        uint32_t n[4];
        ldsm4(n, addr);
        stsm4(addr, &xr[(p * 4 + g) * 4]);
#pragma unroll
        for (int i = 0; i < 4; i++) xr[(p * 4 + g) * 4 + i] = n[i];
      }
      if (half) chunk_staged(p);
    };
    auto chunk_of = [&](int c) { return wg ? (0x7631 >> (c * 4)) & 7 : (0x5420 >> (c * 4)) & 7; };
    auto add_partial = [&](int c) __attribute__((always_inline)) {
      const int n = chunk_of(c);
      const int slot = wg ? (0x1001 >> (c * 4)) & 3 : (0x2120 >> (c * 4)) & 3;
      PROF(768 + wg * 16 + c * 2);
      mbar_spin(sb + BAR_PFULL + n * 8, 0);
      PROF(768 + wg * 16 + c * 2 + 1);
      wg_fence();
      wgmma_n256(acc, ((uint64_t)(128 >> 4) << 32) | ((128 >> 4) << 16) | (((sb + OFF_UNIT + (6 - 2 * c) * 128) & 0x3FFFF) >> 4),
                 ((uint64_t)(256 >> 4) << 32) | ((128 >> 4) << 16) | (((sb + OFF_P + slot * A_SLOT) & 0x3FFFF) >> 4));
    };
    auto issue = [&](int i, int q, int t, bool wait_b) __attribute__((always_inline)) {
      if (!(i & 1)) mbar_spin(afull + (i >> 1) * 8, q & 1);
      if (wait_b) mbar_spin(sb + (q ? BAR_BFULL : BAR_BFULL0) + i * 8, (q ? q ^ t ^ 1 : t) & 1);
      const uint64_t adesc = adesc_q + ((i >> 1) * (A_SLOT >> 4) + (i & 1) * 4);
      const uint64_t bdesc = bdesc_q + i * (B_SLOT >> 4);
      wg_fence();
      wgmma_n256(acc, adesc, bdesc);
      wgmma_n256(acc, adesc + 2, bdesc + 128);
      wg_commit();
      if (i == NB - 1) { adesc_q += zero; bdesc_q += zero; }
    };
    auto retire = [&](int i, bool with_a) {
      wg_wait<2>();
      release((i + 6) & 7, with_a);
    };
    auto k_loop = [&](auto first, int t) __attribute__((always_inline)) {
      constexpr bool FIRST = decltype(first)::value;
      const bool inject = FIRST && brief && !helper;
      const uint32_t up = moves_up(t) ? B_SLOT >> 4 : 0;
      auto extras = [&](int q, int i, bool swap_now) __attribute__((always_inline)) {
        if (!FIRST) return;
        if (swap_now) swap_half(((i + 5) >> 1) & 3, (i + 1) & 1);
        if (!(i & 1) && q == capture_q) capture_slot(i >> 1);
      };
      auto free_partial = [&](int c) {
        if (FIRST) mbar_arrive_if(sb + BAR_PFREE + chunk_of(c) * 8, inject && rel_b);
      };
      extras(0, 0, false);
#pragma unroll
      for (int i = 1; i < 8; i++) {
        if (!(i & 1)) PROF(t * 32 + wg * 16 + 8 + (i >> 1));
        if ((i == 1 || i == 7) && inject) add_partial(i >> 2);
        issue(i, 0, t, true);
        if (i >= 2) retire(i, rel_ab);
        if (i == 3) free_partial(0);
        extras(0, i, i >= 3 && swap);
      }
      PROF(t * 32 + wg * 16 + 1);
      if (!FIRST || !brief) {
#pragma unroll 1
        for (int q = 1; q < 3; q++) {
#pragma unroll
          for (int i = 0; i < 8; i++) {
            issue(i, q | 4, t, true);
            if (i == 0) PROF(t * 32 + wg * 16 + 3 + q);
            retire(i, rel_ab);
            extras(q, i, i < 3 && swap);
          }
          if (FIRST) swap = false;
          if (q == 1) bdesc_q += up;
        }
      }
      const bool rel_last = rel_b | (hold & rel_ab);
      auto with_a = [&](int slot) { return slot == 7 ? rel_ab : rel_last; };
      constexpr int JOIN = DRAIN + 2;
      constexpr int INJ = JOIN < 3 ? 3 : JOIN;
#pragma unroll
      for (int i = 0; i < DRAIN; i++) {
        issue(i, 3, t, true);
        retire(i, with_a((i + 6) & 7));
        if (i == 1) free_partial(1);
        extras(3, i, i < 3 && swap);
      }
      if (wg == 1) {
        wg_wait<1>();
        release((DRAIN + 6) & 7, with_a((DRAIN + 6) & 7));
        wg_wait<0>();
        release((DRAIN + 7) & 7, with_a((DRAIN + 7) & 7));
        if (DRAIN < 2) free_partial(1);
        PROF(t * 32 + wg * 16 + 12);
#pragma unroll
        for (int i = DRAIN; i < 3; i++) extras(-2, i, swap);
        mbar_spin(sb + BAR_ORDER, t & 1);
        PROF(t * 32 + wg * 16 + 6);
#pragma unroll
        for (int i = DRAIN; i < JOIN; i++) {
          issue(i, 3, t, true);
          extras(3, i, false);
        }
      } else {
        PROF(t * 32 + wg * 16 + 6);
#pragma unroll
        for (int i = DRAIN; i < JOIN; i++) {
          issue(i, 3, t, true);
          retire(i, with_a((i + 6) & 7));
          if (i == 1) free_partial(1);
          extras(3, i, i < 3 && swap);
        }
      }
#pragma unroll
      for (int i = JOIN; i < 8; i++) {
        if ((i == INJ || i == 7) && inject) add_partial(i == INJ ? 2 : 3);
        issue(i, 3, t, true);
        if (i == 7) mbar_arrive_if(sb + BAR_ORDER, rel_b & (wg == 0));
        retire(i, rel_last);
        if (i == INJ + 2) free_partial(2);
        extras(3, i, false);
      }
      bdesc_q -= up;
    };

    auto epilogue = [&](auto kind, int t, bool more) __attribute__((always_inline)) {
      constexpr int KIND = decltype(kind)::value;
      constexpr int PRE = KIND == 0 ? BPRE : (KIND == 1 ? HPRE : 0);
      if (KIND != 1 && t == 0) mbar_spin(sb + BAR_BIAS, 0);
      const uint32_t bl = sb + OFF_BIAS + (KIND == 1 ? kLayers - 1 : l) * 512 + ((frag0 >> 3) & 0x30);
      uint32_t bq[8][4];
      auto load_bias = [&](int U) {
        asm volatile("ld.shared.v4.u32 {%0, %1, %2, %3}, [%4];"
                     : "=r"(bq[U][0]), "=r"(bq[U][1]), "=r"(bq[U][2]), "=r"(bq[U][3]) : "r"(bl + U * 64));
      };
#pragma unroll
      for (int U = 0; U < PRE; U++) load_bias(U);
      wg_wait<1>();
      release(6, false);
      if (more) mbar_spin(sb + BAR_BFULL0, (t + 1) & 1);
      wg_wait<0>();
#pragma unroll
      for (int i = 0; i < 128; i++) asm volatile("" : "+f"(acc[i]) :: "memory");
      release(7, KIND == 0 ? rel_b : (KIND == 1 ? rel_ab : rel_b | (more & rel_ab)));
      PROF(t * 32 + wg * 16 + 2);
      if (t == 0) PROF_ST(30 + wg);

      auto pack = [&](int i, float off) {
        uint32_t v;
        asm("cvt.rn.bf16x2.f32 %0, %1, %2;" : "=r"(v) : "f"(acc[i * 2 + 1] - off), "f"(acc[i * 2] - off));
        return v;
      };
      auto cross = [&](int T, int i, float off) {
        uint32_t s2 = pack(T * 4 + i, off), o;
        asm("add.rn.bf16x2 %0, %1, %2;" : "=r"(s2) : "r"(s2), "r"(bq[T >> 1][(T & 1) * 2 + (i >> 1)]));
        asm("fma.rn.bf16x2 %0, %1, %2, %1;" : "=r"(o) : "r"(xr[T * 4 + i]), "r"(s2));
        return o;
      };
      auto reset = [&](int T) {
#pragma unroll
        for (int i = T * 8; i < T * 8 + 8; i += 4)
          asm volatile("ld.volatile.shared.v4.f32 {%0, %1, %2, %3}, [%4];"
                       : "+f"(acc[i]), "+f"(acc[i + 1]), "+f"(acc[i + 2]), "+f"(acc[i + 3]) : "r"(sb + OFF_INIT));
      };
      auto offset_for = [&](int T) { return T >= LAG ? acc[(T - LAG) * 8 + 7] : kOffset; };
      if (KIND == 2) {
        uint32_t id;
        asm volatile("mov.u32 %0, %%tid.x;" : "=r"(id));
        __nv_bfloat16* dst = optr + (size_t)(job_row(t) + wg * 64) * kDim + j * 256 + (id & 127) * 2;
        uint64_t pol;
        asm volatile("createpolicy.fractional.L2::evict_first.b64 %0, 1.0;" : "=l"(pol));
#pragma unroll
        for (int T = 0; T < 16; T++) {
#pragma unroll
          for (int i = 0; i < 4; i++)
            asm volatile("st.global.L2::cache_hint.b32 [%0], %1, %2;"
                         ::"l"(dst + (T * 4 + (i ^ 1)) * kDim), "r"(pack(T * 4 + i, offset_for(T))), "l"(pol) : "memory");
          reset(T);
        }
        asm volatile("bar.sync %0, 128;" ::"r"(wg + 1) : "memory");
        mbar_arrive_if(sb + BAR_PUB + wg * 8, rel_b);
      } else if (KIND == 1) {
#pragma unroll
        for (int T = 0; T < 16; T++) {
#pragma unroll
          for (int i = 0; i < 4; i++) xr[T * 4 + i] = cross(T, i, offset_for(T));
          if ((T & 1) && (T >> 1) + PRE < 8) load_bias((T >> 1) + PRE);
          reset(T);
        }
      } else {
#pragma unroll
        for (int T = 0; T < 16; T++) {
          uint32_t o[4];
#pragma unroll
          for (int i = 0; i < 4; i++) o[i] = cross(T, i, kOffset);
          stsm4((frag0 ^ ((T & 3) * 32)) + (T >> 2) * A_SLOT, o);
          if ((T & 3) == 3) chunk_staged(T >> 2);
          if ((T & 1) && (T >> 1) + PRE < 8) load_bias((T >> 1) + PRE);
        }
        PROF(t * 32 + wg * 16 + 7);
      }
      PROF(t * 32 + wg * 16 + 3);
    };

    PROF_ST(8);
    cluster_wait();
    PROF_ST(9);
    mbar_spin(sb + BAR_BFULL0, 0);
    PROF_ST(10);
    int t = 0;
#pragma unroll 1
    while (true) {
      if (t > 0) {
        if (helper) {
          epilogue(Int<2>(), t - 1, t < kJobs);
          if (t == kJobs) break;
        } else {
          epilogue(Int<1>(), t - 1, true);
        }
      }
      issue(0, 0, 0, false);
      if (t == 0) PROF_ST(11);
      l = 0;
      swap = t > 0 && !helper;
      brief = helper || t == short_t;
      hold = helper && t + 1 < kJobs;
      capture_q = (t > 0 || helper) ? -1 : j;
      PROF(t * 32 + wg * 16 + 0);
      k_loop(Flag<true>(), t);
      t++;
      if (helper) continue;
#pragma unroll 1
      do {
        epilogue(Int<0>(), t - 1, t < kTiles);
        if (t == kTiles) asm volatile("exit;");
        issue(0, 0, 0, false);
        l++;
        hold = l == kLayers - 1 && t + 1 < kTiles;
        PROF(t * 32 + wg * 16 + 0);
        k_loop(Flag<false>(), t);
        t++;
      } while (!hold);
    }
  }
}

__global__ void __launch_bounds__(256) dcn_fallback(const __nv_bfloat16* __restrict__ x0, const __nv_bfloat16* __restrict__ w,
                                                    const __nv_bfloat16* __restrict__ b, __nv_bfloat16* __restrict__ out) {
  __shared__ float xs[8][kDim];
  const size_t r0 = (size_t)blockIdx.x * 8;
  for (int i = threadIdx.x; i < 8 * kDim; i += 256) xs[i / kDim][i % kDim] = __bfloat162float(x0[r0 * kDim + i]);
  __syncthreads();
  for (int l = 0; l < kLayers; l++) {
    float a[4][8] = {};
    for (int k = 0; k < kDim; k++) {
#pragma unroll
      for (int c = 0; c < 4; c++) {
        const float wv = __bfloat162float(w[((size_t)l * kDim + k) * kDim + c * 256 + threadIdx.x]);
#pragma unroll
        for (int r = 0; r < 8; r++) a[c][r] += xs[r][k] * wv;
      }
    }
    __syncthreads();
#pragma unroll
    for (int c = 0; c < 4; c++) {
      const int n = c * 256 + threadIdx.x;
#pragma unroll
      for (int r = 0; r < 8; r++) {
        const float v = __bfloat162float(x0[(r0 + r) * kDim + n]) * (a[c][r] + __bfloat162float(b[l * kDim + n])) + xs[r][n];
        xs[r][n] = __bfloat162float(__float2bfloat16(v));
      }
    }
    __syncthreads();
  }
  for (int i = threadIdx.x; i < 8 * kDim; i += 256) out[r0 * kDim + i] = __float2bfloat16(xs[i / kDim][i % kDim]);
}

typedef CUresult (*EncodeFn)(CUtensorMap*, CUtensorMapDataType, cuuint32_t, void*, const cuuint64_t*, const cuuint64_t*,
                             const cuuint32_t*, const cuuint32_t*, CUtensorMapInterleave, CUtensorMapSwizzle,
                             CUtensorMapL2promotion, CUtensorMapFloatOOBfill);

static void make_map_2d(EncodeFn enc, CUtensorMap* m, void* ptr, uint64_t rows, uint32_t box_rows,
                        CUtensorMapSwizzle swizzle = CU_TENSOR_MAP_SWIZZLE_128B) {
  cuuint64_t dims[2] = {(cuuint64_t)kDim, rows};
  cuuint64_t strides[1] = {kDim * 2};
  cuuint32_t box[2] = {64, box_rows};
  cuuint32_t es[2] = {1, 1};
  enc(m, CU_TENSOR_MAP_DATA_TYPE_BFLOAT16, 2, ptr, dims, strides, box, es, CU_TENSOR_MAP_INTERLEAVE_NONE,
      swizzle, CU_TENSOR_MAP_L2_PROMOTION_L2_128B, CU_TENSOR_MAP_FLOAT_OOB_FILL_NONE);
}

}

extern "C" void kernel_launch(void* const* d_in, const int* in_sizes, int n_in, void* d_out, int out_size) {
  using namespace dcn;
  (void)in_sizes; (void)n_in; (void)out_size;
  void* fn = nullptr;
  cudaDriverEntryPointQueryResult qr;
  cudaGetDriverEntryPoint("cuTensorMapEncodeTiled", &fn, cudaEnableDefault, &qr);
  EncodeFn enc = (EncodeFn)fn;
  CUtensorMap mx64, mx32, mo64, mo32, mw, mp;
  make_map_2d(enc, &mx64, d_in[0], kRows, 64);
  make_map_2d(enc, &mx32, d_in[0], kRows, 32);
  make_map_2d(enc, &mo64, d_out, kRows, 64);
  make_map_2d(enc, &mo32, d_out, kRows, 32);
  make_map_2d(enc, &mp, d_out, kRows, 64, CU_TENSOR_MAP_SWIZZLE_NONE);
  {
    cuuint64_t dims[3] = {64, (cuuint64_t)kLayers * kDim, kDim / 64};
    cuuint64_t strides[2] = {kDim * 2, 128};
    cuuint32_t box[3] = {64, 32, 4};
    cuuint32_t es[3] = {1, 1, 1};
    enc(&mw, CU_TENSOR_MAP_DATA_TYPE_BFLOAT16, 3, d_in[1], dims, strides, box, es, CU_TENSOR_MAP_INTERLEAVE_NONE,
        CU_TENSOR_MAP_SWIZZLE_128B, CU_TENSOR_MAP_L2_PROMOTION_L2_128B, CU_TENSOR_MAP_FLOAT_OOB_FILL_NONE);
  }
  const __nv_bfloat16* x0 = (const __nv_bfloat16*)d_in[0];
  const __nv_bfloat16* w = (const __nv_bfloat16*)d_in[1];
  const __nv_bfloat16* b = (const __nv_bfloat16*)d_in[2];
  __nv_bfloat16* out = (__nv_bfloat16*)d_out;
  constexpr int smem = SMEM_BYTES + PROF_SMEM;
  cudaFuncSetAttribute(dcn_kernel, cudaFuncAttributeMaxDynamicSharedMemorySize, smem);

  cudaLaunchConfig_t cfg = {};
  cfg.gridDim = dim3(4 * kGroups + 4);
  cfg.blockDim = dim3(384);
  cfg.dynamicSmemBytes = smem;
  cudaLaunchAttribute attr;
  attr.id = cudaLaunchAttributeClusterDimension;
  attr.val.clusterDim.x = 2;
  attr.val.clusterDim.y = 1;
  attr.val.clusterDim.z = 1;
  cfg.attrs = &attr;
  cfg.numAttrs = 1;
  int clusters = 0;
  cudaOccupancyMaxActiveClusters(&clusters, dcn_kernel, &cfg);
  if (clusters >= 2 * kGroups) {
    const int grid = 4 * kGroups + (clusters >= 2 * kGroups + 2 ? 4 : 0);
    dcn_kernel<<<grid, 384, smem>>>(x0, w, b, out, mx64, mx32, mo64, mo32, mw, mp);
  } else {
    dcn_fallback<<<kRows / 8, 256>>>(x0, w, b, out);
  }
}
```

```cpp
#include <cuda_runtime.h>
#include <cuda.h>
#include <cuda_bf16.h>
#include <stdint.h>

namespace dcn {

__device__ __forceinline__ void wgmma_n256(float (&d)[128], uint64_t da, uint64_t db) {
  asm volatile("wgmma.mma_async.sync.aligned.m64n256k16.f32.bf16.bf16 "
    "{%0, %1, %2, %3, %4, %5, %6, %7, %8, %9, %10, %11, %12, %13, %14, %15, %16, %17, %18, %19, %20, %21, %22, %23, %24, %25, %26, %27, %28, %29, %30, %31, %32, %33, %34, %35, %36, %37, %38, %39, %40, %41, %42, %43, %44, %45, %46, %47, %48, %49, %50, %51, %52, %53, %54, %55, %56, %57, %58, %59, %60, %61, %62, %63, %64, %65, %66, %67, %68, %69, %70, %71, %72, %73, %74, %75, %76, %77, %78, %79, %80, %81, %82, %83, %84, %85, %86, %87, %88, %89, %90, %91, %92, %93, %94, %95, %96, %97, %98, %99, %100, %101, %102, %103, %104, %105, %106, %107, %108, %109, %110, %111, %112, %113, %114, %115, %116, %117, %118, %119, %120, %121, %122, %123, %124, %125, %126, %127}, "
    "%128, %129, 1, 1, 1, 0, 1;\n"
    : "+f"(d[0]), "+f"(d[1]), "+f"(d[2]), "+f"(d[3]), "+f"(d[4]), "+f"(d[5]), "+f"(d[6]), "+f"(d[7]), "+f"(d[8]), "+f"(d[9]), "+f"(d[10]), "+f"(d[11]), "+f"(d[12]), "+f"(d[13]), "+f"(d[14]), "+f"(d[15]), "+f"(d[16]), "+f"(d[17]), "+f"(d[18]), "+f"(d[19]), "+f"(d[20]), "+f"(d[21]), "+f"(d[22]), "+f"(d[23]), "+f"(d[24]), "+f"(d[25]), "+f"(d[26]), "+f"(d[27]), "+f"(d[28]), "+f"(d[29]), "+f"(d[30]), "+f"(d[31]), "+f"(d[32]), "+f"(d[33]), "+f"(d[34]), "+f"(d[35]), "+f"(d[36]), "+f"(d[37]), "+f"(d[38]), "+f"(d[39]), "+f"(d[40]), "+f"(d[41]), "+f"(d[42]), "+f"(d[43]), "+f"(d[44]), "+f"(d[45]), "+f"(d[46]), "+f"(d[47]), "+f"(d[48]), "+f"(d[49]), "+f"(d[50]), "+f"(d[51]), "+f"(d[52]), "+f"(d[53]), "+f"(d[54]), "+f"(d[55]), "+f"(d[56]), "+f"(d[57]), "+f"(d[58]), "+f"(d[59]), "+f"(d[60]), "+f"(d[61]), "+f"(d[62]), "+f"(d[63]), "+f"(d[64]), "+f"(d[65]), "+f"(d[66]), "+f"(d[67]), "+f"(d[68]), "+f"(d[69]), "+f"(d[70]), "+f"(d[71]), "+f"(d[72]), "+f"(d[73]), "+f"(d[74]), "+f"(d[75]), "+f"(d[76]), "+f"(d[77]), "+f"(d[78]), "+f"(d[79]), "+f"(d[80]), "+f"(d[81]), "+f"(d[82]), "+f"(d[83]), "+f"(d[84]), "+f"(d[85]), "+f"(d[86]), "+f"(d[87]), "+f"(d[88]), "+f"(d[89]), "+f"(d[90]), "+f"(d[91]), "+f"(d[92]), "+f"(d[93]), "+f"(d[94]), "+f"(d[95]), "+f"(d[96]), "+f"(d[97]), "+f"(d[98]), "+f"(d[99]), "+f"(d[100]), "+f"(d[101]), "+f"(d[102]), "+f"(d[103]), "+f"(d[104]), "+f"(d[105]), "+f"(d[106]), "+f"(d[107]), "+f"(d[108]), "+f"(d[109]), "+f"(d[110]), "+f"(d[111]), "+f"(d[112]), "+f"(d[113]), "+f"(d[114]), "+f"(d[115]), "+f"(d[116]), "+f"(d[117]), "+f"(d[118]), "+f"(d[119]), "+f"(d[120]), "+f"(d[121]), "+f"(d[122]), "+f"(d[123]), "+f"(d[124]), "+f"(d[125]), "+f"(d[126]), "+f"(d[127])
    : "l"(da), "l"(db));
}

constexpr int kDim = 1024;
constexpr int kRows = 16384;
constexpr int kLayers = 6;
constexpr int kGroups = 32;
constexpr int kRounds = kRows / 128 / kGroups;
constexpr int kTiles = kRounds * kLayers;

constexpr int kJobs = kGroups;
constexpr int kEpoch = 32;
constexpr int NA = 4;
constexpr int NB = 8;
constexpr float kOffset = 85.333336f;
constexpr float kTrunc = 64 * 0.375f / 131072;
constexpr int DRAIN = 1;
constexpr int LAG = 3;
constexpr int BPRE = 5;
constexpr int HPRE = 6;
constexpr uint32_t kAlign = 0x412a;
constexpr int NF = 2;
constexpr int A_SLOT = 8192;
constexpr int B_SLOT = 16384;
constexpr int OFF_B = 0;
constexpr int NP = 3;
constexpr int OFF_P = OFF_B + NB * B_SLOT;
constexpr int OFF_A = OFF_P + NP * A_SLOT;
constexpr int OFF_UNIT = OFF_A + 2 * NA * A_SLOT;
constexpr int OFF_BIAS = OFF_UNIT + 2048;
constexpr int OFF_INIT = OFF_BIAS + kLayers * 256 * 2;
constexpr int OFF_DELAY = OFF_INIT + 16;
constexpr int OFF_BAR = OFF_DELAY + 16;
constexpr int BAR_BFULL = OFF_BAR;
constexpr int BAR_BFULL0 = BAR_BFULL + NB * 8;
constexpr int BAR_BEMPTY = BAR_BFULL0 + NB * 8;
constexpr int BAR_AFULL = BAR_BEMPTY + NB * 8;
constexpr int BAR_AEMPTY = BAR_AFULL + 2 * NA * 8;
constexpr int BAR_XREADY = BAR_AEMPTY + 2 * NA * 8;
constexpr int BAR_PUB = BAR_XREADY + 16;
constexpr int BAR_PFULL = BAR_PUB + 16;
constexpr int BAR_PFREE = BAR_PFULL + 8 * 8;
constexpr int BAR_STAGED = BAR_PFREE + 8 * 8;
constexpr int BAR_ORDER = BAR_STAGED + 2 * NA * 8;
constexpr int BAR_BIAS = BAR_ORDER + 8;
constexpr int SMEM_BYTES = BAR_BIAS + 8;
static_assert(SMEM_BYTES <= 232448, "shared memory budget");

constexpr int kFlagSet = 4 * (kGroups + 1) * 32;
__device__ unsigned int g_flags[3 * kFlagSet];
__device__ unsigned long long g_phase[16 * 32];

__device__ __forceinline__ uint32_t smem_u32(const void* p) { return (uint32_t)__cvta_generic_to_shared(p); }
__device__ __forceinline__ void mbar_init(uint32_t bar, int cnt) {
  asm volatile("mbarrier.init.shared::cta.b64 [%0], %1;" ::"r"(bar), "r"(cnt) : "memory");
}
__device__ __forceinline__ void mbar_arrive(uint32_t bar) {
  asm volatile("mbarrier.arrive.shared::cta.b64 _, [%0];" ::"r"(bar) : "memory");
}
__device__ __forceinline__ uint32_t map_cta(uint32_t addr, uint32_t cta) {
  uint32_t r;
  asm volatile("mapa.shared::cluster.u32 %0, %1, %2;" : "=r"(r) : "r"(addr), "r"(cta));
  return r;
}
__device__ __forceinline__ void mbar_arrive_mapped_if(uint32_t cluster_addr, bool pred) {
  asm volatile("{\n.reg .pred p;\nsetp.ne.u32 p, %1, 0;\n@p mbarrier.arrive.shared::cluster.b64 _, [%0];\n}"
               ::"r"(cluster_addr), "r"((uint32_t)pred) : "memory");
}
__device__ __forceinline__ void mbar_arrive_if(uint32_t bar, bool pred) {
  asm volatile("{\n.reg .pred p;\nsetp.ne.u32 p, %1, 0;\n@p mbarrier.arrive.shared::cta.b64 _, [%0];\n}"
               ::"r"(bar), "r"((uint32_t)pred) : "memory");
}
__device__ __forceinline__ void mbar_wait(uint32_t bar, uint32_t parity) {
  asm volatile(
      "{\n.reg .pred p;\n.reg .u32 c;\n"
      "mbarrier.try_wait.parity.shared::cta.b64 p, [%0], %1;\n"
      "@p bra DONE;\n"
      "mov.u32 c, 0;\n"
      "LOOP:\n"
      "mbarrier.try_wait.parity.shared::cta.b64 p, [%0], %1;\n"
      "@p bra DONE;\n"
      "add.u32 c, c, 1;\n"
      "setp.lt.u32 p, c, 1048576;\n"
      "@p bra LOOP;\n"
      "trap;\n"
      "DONE:\n}"
      ::"r"(bar), "r"(parity) : "memory");
}
__device__ __forceinline__ void mbar_spin(uint32_t bar, uint32_t parity) {
  asm volatile(
      "{\n.reg .pred p;\n"
      "LOOP:\n"
      "mbarrier.try_wait.parity.shared::cta.b64 p, [%0], %1;\n"
      "@!p bra LOOP;\n}"
      ::"r"(bar), "r"(parity) : "memory");
}
#define ELECT_BEGIN "{\n.reg .pred e;\nelect.sync _|e, 0xffffffff;\n"
template <bool STREAM> __device__ __forceinline__ void expect_load_2d_e(uint32_t dst, const CUtensorMap* m, uint32_t bar, int c0, int c1) {
  if (STREAM) {
    asm volatile(ELECT_BEGIN ".reg .b64 pol;\ncreatepolicy.fractional.L2::evict_first.b64 pol, 1.0;\n"
                 "@e mbarrier.arrive.expect_tx.shared::cta.b64 _, [%2], 8192;\n"
                 "@e cp.async.bulk.tensor.2d.shared::cluster.global.mbarrier::complete_tx::bytes.L2::cache_hint [%0], [%1, {%3, %4}], [%2], pol;\n}"
                 ::"r"(dst), "l"(m), "r"(bar), "r"(c0), "r"(c1) : "memory");
  } else {
    asm volatile(ELECT_BEGIN
                 "@e mbarrier.arrive.expect_tx.shared::cta.b64 _, [%2], 8192;\n"
                 "@e cp.async.bulk.tensor.2d.shared::cluster.global.mbarrier::complete_tx::bytes [%0], [%1, {%3, %4}], [%2];\n}"
                 ::"r"(dst), "l"(m), "r"(bar), "r"(c0), "r"(c1) : "memory");
  }
}
__device__ __forceinline__ void expect_load_2d_mc_e(uint32_t dst, const CUtensorMap* m, uint32_t bar, int c0, int c1) {
  asm volatile(ELECT_BEGIN ".reg .b64 pol;\ncreatepolicy.fractional.L2::evict_first.b64 pol, 1.0;\n"
               "@e mbarrier.arrive.expect_tx.shared::cta.b64 _, [%2], 8192;\n"
               "@e cp.async.bulk.tensor.2d.shared::cluster.global.mbarrier::complete_tx::bytes.multicast::cluster.L2::cache_hint [%0], [%1, {%3, %4}], [%2], %5, pol;\n}"
               ::"r"(dst), "l"(m), "r"(bar), "r"(c0), "r"(c1), "h"((uint16_t)3) : "memory");
}
__device__ __forceinline__ void expect_load_3d_e(uint32_t dst, const CUtensorMap* m, uint32_t bar, int c0, int c1, int c2) {
  asm volatile(ELECT_BEGIN
               "@e mbarrier.arrive.expect_tx.shared::cta.b64 _, [%2], 16384;\n"
               "@e cp.async.bulk.tensor.3d.shared::cluster.global.mbarrier::complete_tx::bytes [%0], [%1, {%3, %4, %5}], [%2];\n}"
               ::"r"(dst), "l"(m), "r"(bar), "r"(c0), "r"(c1), "r"(c2) : "memory");
}
template <bool STREAM> __device__ __forceinline__ void store_2d_e(const CUtensorMap* m, uint32_t src, int c0, int c1) {
  if (STREAM) {
    asm volatile(ELECT_BEGIN ".reg .b64 pol;\ncreatepolicy.fractional.L2::evict_first.b64 pol, 1.0;\n"
                 "@e cp.async.bulk.tensor.2d.global.shared::cta.bulk_group.L2::cache_hint [%0, {%2, %3}], [%1], pol;\n}"
                 ::"l"(m), "r"(src), "r"(c0), "r"(c1) : "memory");
  } else {
    asm volatile(ELECT_BEGIN
                 "@e cp.async.bulk.tensor.2d.global.shared::cta.bulk_group [%0, {%2, %3}], [%1];\n}"
                 ::"l"(m), "r"(src), "r"(c0), "r"(c1) : "memory");
  }
}
__device__ __forceinline__ void prefetch_2d_e(const CUtensorMap* m, int c0, int c1) {
  asm volatile(ELECT_BEGIN
               "@e cp.async.bulk.prefetch.tensor.2d.L2.global [%0, {%1, %2}];\n}"
               ::"l"(m), "r"(c0), "r"(c1) : "memory");
}
__device__ __forceinline__ void prefetch_1d_e(const void* ptr, uint32_t bytes) {
  asm volatile(ELECT_BEGIN
               "@e cp.async.bulk.prefetch.L2.global [%0], %1;\n}"
               ::"l"(ptr), "r"(bytes) : "memory");
}
__device__ __forceinline__ void paced_load_3d_e(uint32_t dst, const CUtensorMap* m, uint32_t bar, int c0, int c1, int c2, bool pace) {
  asm volatile(ELECT_BEGIN ".reg .pred p;\nsetp.ne.u32 p, %6, 0;\n"
               "@e mbarrier.arrive.expect_tx.shared::cta.b64 _, [%2], 16384;\n"
               "@p nanosleep.u32 128;\n"
               "@e cp.async.bulk.tensor.3d.shared::cluster.global.mbarrier::complete_tx::bytes [%0], [%1, {%3, %4, %5}], [%2];\n}"
               ::"r"(dst), "l"(m), "r"(bar), "r"(c0), "r"(c1), "r"(c2), "r"((uint32_t)pace) : "memory");
}
__device__ __forceinline__ void arrive_mapped_e(uint32_t cluster_addr) {
  asm volatile(ELECT_BEGIN "@e mbarrier.arrive.shared::cluster.b64 _, [%0];\n}" ::"r"(cluster_addr) : "memory");
}
__device__ __forceinline__ void arrive_e(uint32_t bar) {
  asm volatile(ELECT_BEGIN "@e mbarrier.arrive.shared::cta.b64 _, [%0];\n}" ::"r"(bar) : "memory");
}
__device__ __forceinline__ void bulk_commit() { asm volatile("cp.async.bulk.commit_group;" ::: "memory"); }
template <int N> __device__ __forceinline__ void bulk_wait() { asm volatile("cp.async.bulk.wait_group %0;" ::"n"(N) : "memory"); }
__device__ __forceinline__ void wg_fence() { asm volatile("wgmma.fence.sync.aligned;" ::: "memory"); }
__device__ __forceinline__ void wg_commit() { asm volatile("wgmma.commit_group.sync.aligned;" ::: "memory"); }
template <int N> __device__ __forceinline__ void wg_wait() { asm volatile("wgmma.wait_group.sync.aligned %0;" ::"n"(N) : "memory"); }
__device__ __forceinline__ void fence_async_global() { asm volatile("fence.proxy.async.global;" ::: "memory"); }
__device__ __forceinline__ void st_relaxed(unsigned int* p, unsigned int v) {
  asm volatile("st.relaxed.gpu.global.u32 [%0], %1;" ::"l"(p), "r"(v) : "memory");
}
__device__ __forceinline__ void ldsm4(uint32_t* r, uint32_t addr) {
  asm volatile("ldmatrix.sync.aligned.m8n8.x4.shared.b16 {%0, %1, %2, %3}, [%4];"
               : "=r"(r[0]), "=r"(r[1]), "=r"(r[2]), "=r"(r[3]) : "r"(addr) : "memory");
}
__device__ __forceinline__ void stsm4(uint32_t addr, const uint32_t* r) {
  asm volatile("stmatrix.sync.aligned.m8n8.x4.shared.b16 [%0], {%1, %2, %3, %4};"
               ::"r"(addr), "r"(r[0]), "r"(r[1]), "r"(r[2]), "r"(r[3]) : "memory");
}
template <bool V> struct Flag { static constexpr bool value = V; };
template <int V> struct Int { static constexpr int value = V; };
__device__ __forceinline__ void fence_async_smem() { asm volatile("fence.proxy.async.shared::cta;" ::: "memory"); }
__device__ __forceinline__ void cluster_arrive_relaxed() { asm volatile("barrier.cluster.arrive.relaxed.aligned;" ::: "memory"); }
__device__ __forceinline__ void cluster_wait() { asm volatile("barrier.cluster.wait.acquire.aligned;" ::: "memory"); }
__device__ __forceinline__ void prefetch_map(const CUtensorMap* m) {
  asm volatile("prefetch.tensormap [%0];" ::"l"(m) : "memory");
}
__device__ __forceinline__ void prefetch_map_e(const CUtensorMap* m) {
  asm volatile(ELECT_BEGIN "@e prefetch.tensormap [%0];\n}" ::"l"(m) : "memory");
}
__device__ __forceinline__ void poll_flag(const unsigned int* ptr, unsigned int target) {
  asm volatile(
      "{\n.reg .pred p;\n.reg .u32 c;\n.reg .s32 v;\n"
      "mov.u32 c, 0;\n"
      "LOOP:\n"
      "ld.acquire.gpu.global.s32 v, [%0];\n"
      "sub.s32 v, v, %1;\n"
      "setp.ge.s32 p, v, 0;\n"
      "@p bra DONE;\n"
      "add.u32 c, c, 1;\n"
      "setp.lt.u32 p, c, 1048576;\n"
      "@p bra LOOP;\n"
      "trap;\n"
      "DONE:\n}"
      ::"l"(ptr), "r"(target) : "memory");
}

constexpr uint32_t DESC_HI = (1024u >> 4) | (1u << 30);
__device__ __forceinline__ uint64_t desc(uint32_t lo) { return ((uint64_t)DESC_HI << 32) | lo; }
constexpr uint32_t DESC_A_LBO = 1u << 16;
constexpr uint32_t DESC_B_LBO = (4096u >> 4) << 16;

__device__ __forceinline__ int kgroup_col(int j, int q) {
  return q == 0 ? j : (q == 1 ? (j ^ 1) : (((j ^ 2) & ~1) + (q - 2)));
}

__device__ __forceinline__ int role_of_cluster(int c) {
  const int a = c - 4;
  const int b = c - 36, r = (b * 37) >> 8;
  const int first = (a & ~7) + (a & 3) * 2 + ((a >> 2) & 1);
  const int second = 32 + r * 8 + ((0x7531640 >> (((b - r * 7) * 4) & 31)) & 7);
  return c >= 2 * kGroups ? c : (c >= 36 ? second : (c >= 4 ? first : 34 + c * 8));
}
__device__ __forceinline__ int helped_round(int grp) { return (grp & 2) ? (grp & 3) - 1 : 3; }
__device__ __forceinline__ int job_of_group(int grp) {
  return (grp & 2) ? (grp & 1) * 8 + (grp >> 2) : 16 + (grp >> 2) * 2 + (grp & 1);
}
__device__ __forceinline__ int job_row(int n) {
  const int grp = n < 16 ? (n & 7) * 4 + 2 + (n >> 3) : ((n - 16) >> 1) * 4 + (n & 1);
  return (helped_round(grp) * kGroups + grp) * 128;
}

constexpr int PROF_SMEM = 0;
#define PROF_BOTH(idx) do {} while (0)
#define PROF_SVC(idx) do {} while (0)
#define PROF_DUMP() do {} while (0)
#define PROF(idx) do {} while (0)
#define PROF_ST(idx) do {} while (0)
#define PROF_SKEW(idx) do {} while (0)

__global__ void __cluster_dims__(2, 1, 1) __launch_bounds__(384, 1)
dcn_kernel(const __nv_bfloat16* __restrict__ xptr, const __nv_bfloat16* __restrict__ wptr,
           const __nv_bfloat16* __restrict__ bias, __nv_bfloat16* optr,
           const __grid_constant__ CUtensorMap mx64, const __grid_constant__ CUtensorMap mx32,
           const __grid_constant__ CUtensorMap mo64, const __grid_constant__ CUtensorMap mo32,
           const __grid_constant__ CUtensorMap mw, const __grid_constant__ CUtensorMap mp) {
  extern __shared__ __align__(1024) uint8_t smem_raw[];
  const uint32_t sb = smem_u32(smem_raw);
  const int tid = threadIdx.x;
  if ((tid >> 5) == 8) PROF_ST(0);
  if ((tid >> 5) == 9) PROF_BOTH(48);
  const int wid = __shfl_sync(0xffffffffu, tid >> 5, 0);
  if (wid == 0) {
    asm volatile("prefetch.global.L2 [%0];" ::"l"(wptr + ((blockIdx.x & 31) * 32 + tid) * 64));
    asm volatile("prefetch.global.L2 [%0];" ::"l"(xptr + ((blockIdx.x & 127) * 32 + tid) * kDim));
    prefetch_map_e(&mw);
    prefetch_map_e(&mx64);
    PROF_ST(29);
  }
  const int bid = role_of_cluster(blockIdx.x >> 1) * 2 + (blockIdx.x & 1);
  const int j = bid & 3;
  const int grp = bid >> 2;
  const bool helper = grp == kGroups;
  const int col0 = helper ? kgroup_col(j, 2) * 256 : 0;
  const int row0 = helper ? job_row(0) : grp * 128;
  auto first_loads = [&](int s) {
    const int col = col0 + s * 64;
    expect_load_3d_e(sb + OFF_B + 2 * s * B_SLOT, &mw, sb + BAR_BFULL0 + 2 * s * 8, 0, col, j * 4);
    expect_load_2d_e<false>(sb + OFF_A + s * A_SLOT, &mx64, sb + BAR_AFULL + s * 8, col, row0);
    expect_load_3d_e(sb + OFF_B + (2 * s + 1) * B_SLOT, &mw, sb + BAR_BFULL0 + (2 * s + 1) * 8, 0, col + 32, j * 4);
    expect_load_2d_e<false>(sb + OFF_A + (NA + s) * A_SLOT, &mx64, sb + BAR_AFULL + (NA + s) * 8, col, row0 + 64);
    PROF_ST(2 + s);
  };
  auto init_full = [&](int s) {
    mbar_init(sb + BAR_BFULL0 + 2 * s * 8, 1);
    mbar_init(sb + BAR_BFULL0 + (2 * s + 1) * 8, 1);
    mbar_init(sb + BAR_AFULL + s * 8, 1);
    mbar_init(sb + BAR_AFULL + (NA + s) * 8, 1);
  };
  if (wid == 8) {
    PROF_ST(28);
    if (tid == 256) {
      init_full(0);
      asm volatile("fence.mbarrier_init.release.cluster;" ::: "memory");
    }
    __syncwarp();
    PROF_ST(1);
    first_loads(0);
    if (tid == 256) {
#pragma unroll
      for (int s = 1; s < 4; s++) init_full(s);
      asm volatile("fence.mbarrier_init.release.cluster;" ::: "memory");
    }
    __syncwarp();
#pragma unroll
    for (int s = 1; s < NF; s++) first_loads(s);
  }
  const int wg = wid >> 2;
  const int warp = wid & 3;
  const uint32_t rank = j & 1;
  const int short_t = (gridDim.x > 4 * kGroups && !helper) ? helped_round(grp) * kLayers : -8;
  const unsigned lend = helper ? ~0u : 1u;
  auto moves_up = [&](int t) { return (unsigned)(t + 1 - short_t) > lend; };

  if (wg == 2) {
    asm volatile("setmaxnreg.dec.sync.aligned.u32 40;");
    if (tid == 288) {
      if (sb & 1023) asm volatile("trap;");
#pragma unroll
      for (int i = 0; i < NB; i++) { mbar_init(sb + BAR_BFULL + i * 8, 1); mbar_init(sb + BAR_BEMPTY + i * 8, 2); }
#pragma unroll
      for (int i = 0; i < 4; i++) mbar_init(sb + BAR_XREADY + i * 8, 1);
      mbar_init(sb + BAR_ORDER, 1);
    } else if (tid == 320) {
#pragma unroll
      for (int i = 0; i < 2 * NA; i++) { mbar_init(sb + BAR_AEMPTY + i * 8, 2); mbar_init(sb + BAR_STAGED + i * 8, 4); }
    } else if (tid == 352) {
#pragma unroll
      for (int i = 0; i < 8; i++) { mbar_init(sb + BAR_PFULL + i * 8, 1); mbar_init(sb + BAR_PFREE + i * 8, 1); }
      mbar_init(sb + BAR_BIAS, 32);
      asm volatile("st.shared.v4.f32 [%0], {%1, %1, %1, %1};" ::"r"(sb + OFF_INIT), "f"(kOffset) : "memory");
      asm volatile("st.shared.v2.u32 [%0], {0, 0};" ::"r"(sb + OFF_DELAY) : "memory");
    }
    asm volatile("fence.mbarrier_init.release.cluster;" ::: "memory");
    __syncwarp();
    cluster_arrive_relaxed();
    if (warp == 0) {
      PROF_ST(6);
#pragma unroll 1
      for (int s = NF; s < 4; s++) first_loads(s);
      cluster_wait();
      PROF_ST(7);
      uint32_t par = 0;
      int l = 0;
      const int ntiles = helper ? kJobs : kTiles;
#pragma unroll 1
      for (int t = 0; t < ntiles; t++) {
        const int jo = (t == 0 && !helper) ? 0 : j;
        const int q_end = t == short_t ? 2 : 4;
#pragma unroll 1
        for (int q = (helper ? 2 : 0) + (t == 0); q < q_end; q++) {
          const int krow = l * kDim + kgroup_col(jo, q) * 256;
          const bool first = q == (helper ? 2 : 0);
          const bool up = q >= 2 && moves_up(t);
          const int shift = first ? (moves_up(t - 1) ? -1 : 0) : (up && q == 2 ? 1 : 0);
          const int paced = first ? (shift ? DRAIN + 1 : 0) : ((helper || (q == 1 && (t == short_t || t == 0))) ? 0 : NB);
          const uint32_t dst = sb + OFF_B + (up ? B_SLOT : 0);
          const uint32_t full = sb + (first ? BAR_BFULL0 : BAR_BFULL);
          if (shift > 0) mbar_spin(sb + BAR_BEMPTY, par);
#pragma unroll 1
          for (int i = 0; i < NB; i++) {
            if ((unsigned)(i + shift) < NB) mbar_spin(sb + BAR_BEMPTY + (i + shift) * 8, par);
            paced_load_3d_e(dst + i * B_SLOT, &mw, full + i * 8, 0, krow + i * 32, j * 4, i < paced);
            PROF_SKEW(t * 32 + q * 8 + i);
          }
          if (shift < 0) mbar_spin(sb + BAR_BEMPTY + (NB - 1) * 8, par);
          par ^= 1;
        }
        if (helper || ++l == kLayers) l = 0;
      }
    } else if (warp <= 2) {
      const int w = warp - 1;
      const uint32_t abase = sb + OFF_A + w * NA * A_SLOT;
      const uint32_t fullb = sb + BAR_AFULL + w * NA * 8;
      const uint32_t emptyb = sb + BAR_AEMPTY + w * 8;
      const uint32_t stagedb = sb + BAR_STAGED + w * NA * 8;
      const unsigned int base = __shfl_sync(0xffffffffu, *(volatile unsigned int*)(g_flags + bid * 32), 0);
      cluster_wait();
      uint32_t epar = 0;
      uint32_t spar = 0;
      auto refill = [&](const CUtensorMap* m, int col, int row) {
#pragma unroll 1
        for (int s = 0; s < 4; s++) {
          mbar_spin(emptyb + s * 16, epar);
          expect_load_2d_e<false>(abase + s * A_SLOT, m, fullb + s * 8, col + s * 64, row);
        }
        epar ^= 1;
      };
      auto store_refill = [&](int out_row, int col, int row, bool last_read) {
#pragma unroll 1
        for (int s = 0; s < 4; s++) {
          mbar_spin(stagedb + s * 8, spar);
          fence_async_smem();
          store_2d_e<true>(&mo64, abase + s * A_SLOT, j * 256 + s * 64, out_row);
          bulk_commit();
          bulk_wait<0>();
          __syncwarp();
          mbar_spin(emptyb + s * 16, epar);
          if (last_read) expect_load_2d_e<true>(abase + s * A_SLOT, &mx64, fullb + s * 8, col + s * 64, row);
          else expect_load_2d_e<false>(abase + s * A_SLOT, &mx64, fullb + s * 8, col + s * 64, row);
        }
        spar ^= 1;
        epar ^= 1;
      };
      auto store_tile = [&](auto stream, int out_row) {
#pragma unroll 1
        for (int c = 0; c < 4; c++) {
          mbar_spin(stagedb + c * 8, spar);
          fence_async_smem();
          arrive_e(fullb + c * 8);
          if (!decltype(stream)::value && w == 1) {
            bulk_commit();
            bulk_wait<0>();
          }
          store_2d_e<decltype(stream)::value>(&mo64, abase + c * A_SLOT, j * 256 + c * 64, out_row);
        }
        spar ^= 1;
        bulk_commit();
        bulk_wait<0>();
        __syncwarp();
      };
      auto refill_shared = [&](const CUtensorMap* m32, int col, int row) {
#pragma unroll 1
        for (int s = 0; s < 4; s++) {
          mbar_spin(emptyb + s * 16, epar);
          expect_load_2d_mc_e(abase + s * A_SLOT + rank * 4096, m32, fullb + s * 8, col + s * 64, row + rank * 32);
        }
        epar ^= 1;
      };
      if (helper) {
#pragma unroll 1
        for (int h = 1; h < 2 * kJobs; h++) refill_shared(&mx32, col0 + (h & 1) * 256, job_row(h >> 1) + w * 64);
      } else {
        const uint32_t xready_peer = map_cta(sb + BAR_XREADY + w * 8, rank ^ 1);
        const unsigned int* oflag = g_flags + (grp * 4 + kgroup_col(j, 2)) * 32;
        unsigned int* done_mine = g_flags + kFlagSet + (bid * 2 + w) * 32;
        const unsigned int* done_peer = g_flags + kFlagSet + ((bid ^ 2) * 2 + w) * 32;
        uint32_t nx = 0;
#pragma unroll 1
        for (int rd = 0; rd < kRounds; rd++) {
          const int xrow = (rd * kGroups + grp) * 128 + w * 64;
          if (rd == 0) {
            refill(&mx64, 256, xrow);
          } else {
            poll_flag(done_peer, base + nx);
            store_refill(xrow - kGroups * 128, (j ^ 1) * 256, xrow, rd * kLayers == short_t);
          }
          if (rd * kLayers != short_t) {
#pragma unroll 1
            for (int h = 0; h < 2; h++) refill_shared(&mx32, (kgroup_col(rd == 0 ? 0 : j, 2) + h) * 256, xrow);
          }
#pragma unroll 1
          for (int l = 1; l < kLayers; l++) {
            if (l > 1) poll_flag(done_peer, base + nx);
            store_tile(Flag<false>(), xrow);
            PROF_SVC((rd * kLayers + l - 1) * 2 + w);
            arrive_mapped_e(xready_peer);
            arrive_e(sb + BAR_PUB + w * 8);
            mbar_spin(sb + BAR_XREADY + w * 8, nx & 1);
            fence_async_global();
            refill(&mo64, (j ^ 1) * 256, xrow);
#pragma unroll 1
            for (int h = 0; h < 2; h++) {
              poll_flag(oflag + h * 32, base + nx + 1);
              fence_async_global();
              refill_shared(&mo32, (kgroup_col(j, 2) + h) * 256, xrow);
            }
            if (rank) {
#pragma unroll 1
              for (int s = 0; s < 4; s++) mbar_spin(fullb + s * 8, 1);
            }
            nx++;
            if ((tid & 31) == 0) st_relaxed(done_mine, base + (nx == kRounds * (kLayers - 1) ? kEpoch : nx));
            __syncwarp();
          }
          const int nrow = xrow + kGroups * 128;
          if (rd + 1 == kRounds) {
            poll_flag(done_peer, base + nx);
            store_tile(Flag<true>(), xrow);
            PROF_SVC((rd * kLayers + kLayers - 1) * 2 + w);
            arrive_e(sb + BAR_PUB + w * 8);
          } else {
            refill(&mx64, j * 256, nrow);
            PROF_SVC((rd * kLayers + kLayers - 1) * 2 + w);
          }
        }
      }
    } else {
      const int lane = tid & 31;
      unsigned int* myflag = g_flags + bid * 32;
      if (lane == 0) { prefetch_map(&mx32); prefetch_map(&mo64); prefetch_map(&mo32); }
      const unsigned int base = *(volatile unsigned int*)myflag;
      auto publish = [&](uint32_t n, uint32_t value) {
#pragma unroll 1
        for (int w = 0; w < 2; w++) mbar_wait(sb + BAR_PUB + w * 8, n & 1);
        if (lane == 0) asm volatile("st.release.gpu.global.u32 [%0], %1;" ::"l"(myflag), "r"(base + value) : "memory");
        __syncwarp();
      };
      if (helper) {
        mbar_arrive(sb + BAR_BIAS);
        cluster_wait();
#pragma unroll 1
        for (int n = 0; n < kJobs; n++) {
          if (n + 2 < kJobs) {
            const int row = job_row(n + 2);
#pragma unroll 1
            for (int i = 0; i < 8; i++) prefetch_2d_e(&mx64, col0 + rank * 256 + (i & 3) * 64, row + (i >> 2) * 64);
          }
          publish(n, n + 1);
        }
      } else {
        {
          float c[8];
#pragma unroll
          for (int i = 0; i < 8; i++) c[i] = 0.f;
#pragma unroll 1
          for (int l = 0; l < kLayers; l++) {
            const uint4 v = *reinterpret_cast<const uint4*>(bias + l * kDim + j * 256 + lane * 8);
            const uint32_t u[4] = {v.x, v.y, v.z, v.w};
#pragma unroll
            for (int i = 0; i < 4; i++) {
              c[2 * i] += __uint_as_float(u[i] << 16) + kTrunc;
              c[2 * i + 1] += __uint_as_float(u[i] & 0xffff0000u) + kTrunc;
              uint32_t pk;
              asm("cvt.rn.bf16x2.f32 %0, %1, %2;" : "=r"(pk) : "f"(c[2 * i + 1]), "f"(c[2 * i]));
              asm volatile("st.shared.u32 [%0], %1;" ::"r"(sb + OFF_BIAS + l * 512 + (lane >> 2) * 64 + i * 16 + (lane & 3) * 4),
                           "r"(pk) : "memory");
            }
          }
#pragma unroll
          for (int i = 0; i < 15; i++) {
            const uint32_t one = (lane >> 3) == (lane & 3) ? 0x3f80u << ((lane & 4) * 4) : 0u;
            asm volatile("st.shared.u32 [%0], %1;" ::"r"(sb + OFF_UNIT + i * 128 + lane * 4), "r"(i == 7 ? one : 0u) : "memory");
          }
          fence_async_smem();
          mbar_arrive(sb + BAR_BIAS);
        }
        const __nv_bfloat16* wslice = wptr + bid * 8192;
        cluster_wait();
        prefetch_1d_e(wslice + kDim * kDim, 16384);
        uint32_t nx = 0;
#pragma unroll 1
        for (int rd = 0; rd < kRounds; rd++) {
#pragma unroll 1
          for (int l = 1; l < kLayers; l++) {
            const int t = rd * kLayers + l;
            const bool align = (kAlign >> t) & 1;
            unsigned long long mine = 0;
            uint32_t tick = 0;
            if (align) {
              uint32_t c0, c1;
              mbar_wait(sb + BAR_ORDER, (t - 1) & 1);
              mbar_wait(sb + BAR_BEMPTY + 56, 0);
              mbar_wait(sb + BAR_BEMPTY + 56, 1);
              asm volatile("mov.u32 %0, %%clock;\nnanosleep.u32 128;\nmov.u32 %1, %%clock;\nmov.u64 %2, %%globaltimer;\n"
                           "nanosleep.u32 128;\nmov.u32 %3, %%clock;"
                           : "=r"(c0), "=r"(c1), "=l"(mine), "=r"(tick) :: "memory");
              tick -= c1;
              mine = ((mine + 64) >> 8 << 10) - (c1 - c0);
            }
            publish(nx, nx + 1 == kRounds * (kLayers - 1) ? kEpoch : nx + 1);
            nx++;
            {
              uint32_t delay = 0;
              if (align) {
                unsigned long long* word = g_phase + (bid & 15) * 32 + t;
                if (lane == 0) atomicMax(word, mine);
                __syncwarp();
#pragma unroll 1
                for (int i = 0; i < 3; i++) __nanosleep(256);
                unsigned long long latest;
                asm volatile("ld.relaxed.gpu.global.u64 %0, [%1];" : "=l"(latest) : "l"(word) : "memory");
                const uint32_t a = (uint32_t)latest, b = (uint32_t)mine;
                const int lag = (int)(((a + 1023) >> 10) - ((b + 1023) >> 10)) * (int)tick - (int)((-a & 1023) - (-b & 1023));
                delay = (lag > 40 && lag < 700) ? lag + 280 : 0;
              }
              asm volatile("st.relaxed.cta.shared.u32 [%0], %1;" ::"r"(sb + OFF_DELAY), "r"(delay) : "memory");
            }
            if (l < kLayers - 1 && rd == 0) prefetch_1d_e(wslice + (l + 1) * kDim * kDim, 16384);
            if (l > 1 && rd + 1 < kRounds) {
              const int nrow = ((rd + 1) * kGroups + grp) * 128;
              prefetch_1d_e(xptr + (size_t)(nrow + j * 32 + l * 8 - 16) * kDim, 8192);
              __nanosleep(600);
              prefetch_1d_e(xptr + (size_t)(nrow + j * 32 + l * 8 - 12) * kDim, 8192);
              if (rd * kLayers + l + 1 == short_t) {
                poll_flag(g_flags + (4 * kGroups + j) * 32, base + job_of_group(grp) + 1);
                fence_async_global();
                constexpr uint32_t order = 0x76325140;
#pragma unroll 1
                for (int i = NP; i < 8; i++)
                  prefetch_2d_e(&mp, j * 256 + ((order >> (i * 4)) & 3) * 64, nrow + ((order >> (i * 4)) & 4) * 16);
#pragma unroll 1
                for (int i = 0; i < 8; i++) {
                  if (i >= NP) mbar_wait(sb + BAR_PFREE + (i - NP) * 8, 0);
                  PROF(776 + i);
                  expect_load_2d_e<true>(sb + OFF_P + (i % NP) * A_SLOT, &mp, sb + BAR_PFULL + i * 8,
                                         j * 256 + ((order >> (i * 4)) & 3) * 64, nrow + ((order >> (i * 4)) & 4) * 16);
                }
              }
            }
          }
        }
#pragma unroll 1
        for (int w = 0; w < 2; w++) mbar_wait(sb + BAR_PUB + w * 8, nx & 1);
      }
    }
    if (warp == 3) PROF_DUMP();
  } else {
    cluster_arrive_relaxed();
    asm volatile("setmaxnreg.inc.sync.aligned.u32 232;");
    PROF_ST(32);
    const int lane = tid & 31;
    const int wtid = tid & 127;
    const uint32_t abase = sb + OFF_A + wg * NA * A_SLOT;
    const uint32_t afull = sb + BAR_AFULL + wg * NA * 8;
    const uint32_t rel = map_cta(sb + (wtid == 64 ? BAR_BEMPTY : BAR_AEMPTY + wg * 8 - 8), wtid == 32 ? (rank ^ 1) : rank);
    const bool rel_b = wtid == 64;
    const bool rel_ab = (wtid & 31) == 0 && wtid < 96;
    const uint32_t frag0 = __shfl_sync(0xffffffffu, abase + ((wtid >> 5) * 16 + ((lane >> 3) & 1) * 8 + (lane & 7)) * 128 +
                                                        (((lane >> 4) ^ (lane & 7)) << 4), lane);
    const uint64_t adesc0 = desc(((abase & 0x3FFFF) >> 4) | DESC_A_LBO);
    const uint64_t bdesc0 = desc((((sb + OFF_B) & 0x3FFFF) >> 4) | DESC_B_LBO);

    const uint64_t zero = gridDim.y - 1;
    uint64_t adesc_q = adesc0 + zero, bdesc_q = bdesc0 + zero;

    float acc[128];
    uint32_t xr[64];
#pragma unroll
    for (int i = 0; i < 128; i++) acc[i] = kOffset;
#pragma unroll
    for (int i = 0; i < 64; i++) xr[i] = 0;
    int l = 0;
    bool hold = false;
    bool swap = false;
    bool brief = helper;
    int capture_q = helper ? -1 : j;

    auto release = [&](int i, bool with_a) {
      mbar_arrive_mapped_if(rel + i * 8, (i & 1) ? with_a : rel_b);
    };
    auto chunk_staged = [&](int c) {
      __syncwarp();
      arrive_e(sb + BAR_STAGED + (wg * NA + c) * 8);
    };
    auto capture_slot = [&](int p) {
#pragma unroll
      for (int g = 0; g < 4; g++) ldsm4(&xr[(p * 4 + g) * 4], (frag0 ^ (g * 32)) + p * A_SLOT);
    };
    auto swap_half = [&](int p, int half) {
#pragma unroll
      for (int g = half * 2; g < half * 2 + 2; g++) {
        const uint32_t addr = (frag0 ^ (g * 32)) + p * A_SLOT;
        uint32_t n[4];
        ldsm4(n, addr);
        stsm4(addr, &xr[(p * 4 + g) * 4]);
#pragma unroll
        for (int i = 0; i < 4; i++) xr[(p * 4 + g) * 4 + i] = n[i];
      }
      if (half) chunk_staged(p);
    };
    auto chunk_of = [&](int c) { return wg ? (0x7631 >> (c * 4)) & 7 : (0x5420 >> (c * 4)) & 7; };
    auto add_partial = [&](int c) __attribute__((always_inline)) {
      const int n = chunk_of(c);
      const int slot = wg ? (0x1001 >> (c * 4)) & 3 : (0x2120 >> (c * 4)) & 3;
      PROF(768 + wg * 16 + c * 2);
      mbar_spin(sb + BAR_PFULL + n * 8, 0);
      PROF(768 + wg * 16 + c * 2 + 1);
      wg_fence();
      wgmma_n256(acc, ((uint64_t)(128 >> 4) << 32) | ((128 >> 4) << 16) | (((sb + OFF_UNIT + (6 - 2 * c) * 128) & 0x3FFFF) >> 4),
                 ((uint64_t)(256 >> 4) << 32) | ((128 >> 4) << 16) | (((sb + OFF_P + slot * A_SLOT) & 0x3FFFF) >> 4));
    };
    auto issue = [&](int i, int q, int t, bool wait_b) __attribute__((always_inline)) {
      if (!(i & 1)) mbar_spin(afull + (i >> 1) * 8, q & 1);
      if (wait_b) mbar_spin(sb + (q ? BAR_BFULL : BAR_BFULL0) + i * 8, (q ? q ^ t ^ 1 : t) & 1);
      const uint64_t adesc = adesc_q + ((i >> 1) * (A_SLOT >> 4) + (i & 1) * 4);
      const uint64_t bdesc = bdesc_q + i * (B_SLOT >> 4);
      wg_fence();
      wgmma_n256(acc, adesc, bdesc);
      wgmma_n256(acc, adesc + 2, bdesc + 128);
      wg_commit();
      if (i == NB - 1) { adesc_q += zero; bdesc_q += zero; }
    };
    auto retire = [&](int i, bool with_a) {
      wg_wait<2>();
      release((i + 6) & 7, with_a);
    };
    auto k_loop = [&](auto first, int t) __attribute__((always_inline)) {
      constexpr bool FIRST = decltype(first)::value;
      const bool inject = FIRST && brief && !helper;
      const uint32_t up = moves_up(t) ? B_SLOT >> 4 : 0;
      auto extras = [&](int q, int i, bool swap_now) __attribute__((always_inline)) {
        if (!FIRST) return;
        if (swap_now) swap_half(((i + 5) >> 1) & 3, (i + 1) & 1);
        if (!(i & 1) && q == capture_q) capture_slot(i >> 1);
      };
      auto free_partial = [&](int c) {
        if (FIRST) mbar_arrive_if(sb + BAR_PFREE + chunk_of(c) * 8, inject && rel_b);
      };
      extras(0, 0, false);
#pragma unroll
      for (int i = 1; i < 8; i++) {
        if (!(i & 1)) PROF(t * 32 + wg * 16 + 8 + (i >> 1));
        if ((i == 1 || i == 7) && inject) add_partial(i >> 2);
        issue(i, 0, t, true);
        if (i >= 2) retire(i, rel_ab);
        if (i == 3) free_partial(0);
        extras(0, i, i >= 3 && swap);
      }
      PROF(t * 32 + wg * 16 + 1);
      if (!FIRST || !brief) {
#pragma unroll 1
        for (int q = 1; q < 3; q++) {
#pragma unroll
          for (int i = 0; i < 8; i++) {
            issue(i, q | 4, t, true);
            if (i == 0) PROF(t * 32 + wg * 16 + 3 + q);
            retire(i, rel_ab);
            extras(q, i, i < 3 && swap);
          }
          if (FIRST) swap = false;
          if (q == 1) bdesc_q += up;
        }
      }
      const bool rel_last = rel_b | (hold & rel_ab);
      auto with_a = [&](int slot) { return slot == 7 ? rel_ab : rel_last; };
      uint32_t delay = 0;
      constexpr int JOIN = DRAIN + 2;
      constexpr int INJ = JOIN < 3 ? 3 : JOIN;
#pragma unroll
      for (int i = 0; i < DRAIN; i++) {
        issue(i, 3, t, true);
        retire(i, with_a((i + 6) & 7));
        if (i == 1) free_partial(1);
        extras(3, i, i < 3 && swap);
      }
      if (wg == 1) {
        wg_wait<1>();
        release((DRAIN + 6) & 7, with_a((DRAIN + 6) & 7));
        wg_wait<0>();
        release((DRAIN + 7) & 7, with_a((DRAIN + 7) & 7));
        if (DRAIN < 2) free_partial(1);
        PROF(t * 32 + wg * 16 + 12);
#pragma unroll
        for (int i = DRAIN; i < 3; i++) extras(-2, i, swap);
        mbar_spin(sb + BAR_ORDER, t & 1);
        PROF(t * 32 + wg * 16 + 6);
#pragma unroll
        for (int i = DRAIN; i < JOIN; i++) {
          issue(i, 3, t, true);
          extras(3, i, false);
        }
      } else {
        PROF(t * 32 + wg * 16 + 6);
#pragma unroll
        for (int i = DRAIN; i < JOIN; i++) {
          issue(i, 3, t, true);
          retire(i, with_a((i + 6) & 7));
          if (i == 1) free_partial(1);
          extras(3, i, i < 3 && swap);
        }
      }
#pragma unroll
      for (int i = JOIN; i < 8; i++) {
        if ((i == INJ || i == 7) && inject) add_partial(i == INJ ? 2 : 3);
        if (!FIRST && i == 3) asm volatile("ld.relaxed.cta.shared.u32 %0, [%1];" : "=r"(delay) : "r"(sb + OFF_DELAY + wg * 4) : "memory");
        if (!FIRST && i == 5) {
          asm volatile("{\n.reg .pred p;\n.reg .u32 a, b;\nsetp.eq.u32 p, %0, 0;\n@p bra.uni DONE;\nmov.u32 a, %%clock;\n"
                       "WAIT:\nmov.u32 b, %%clock;\nsub.u32 b, b, a;\nsetp.lt.u32 p, b, %0;\n@p bra.uni WAIT;\nDONE:\n}" ::"r"(delay) : "memory");
        }
        issue(i, 3, t, true);
        if (i == 7) mbar_arrive_if(sb + BAR_ORDER, rel_b & (wg == 0));
        retire(i, rel_last);
        if (i == INJ + 2) free_partial(2);
        extras(3, i, false);
      }
      bdesc_q -= up;
    };

    auto epilogue = [&](auto kind, int t, bool more) __attribute__((always_inline)) {
      constexpr int KIND = decltype(kind)::value;
      constexpr int PRE = KIND == 0 ? BPRE : (KIND == 1 ? HPRE : 0);
      if (KIND != 1 && t == 0) mbar_spin(sb + BAR_BIAS, 0);
      const uint32_t bl = sb + OFF_BIAS + (KIND == 1 ? kLayers - 1 : l) * 512 + ((frag0 >> 3) & 0x30);
      uint32_t bq[8][4];
      auto load_bias = [&](int U) {
        asm volatile("ld.shared.v4.u32 {%0, %1, %2, %3}, [%4];"
                     : "=r"(bq[U][0]), "=r"(bq[U][1]), "=r"(bq[U][2]), "=r"(bq[U][3]) : "r"(bl + U * 64));
      };
#pragma unroll
      for (int U = 0; U < PRE; U++) load_bias(U);
      wg_wait<1>();
      release(6, false);
      if (more) mbar_spin(sb + BAR_BFULL0, (t + 1) & 1);
      wg_wait<0>();
#pragma unroll
      for (int i = 0; i < 128; i++) asm volatile("" : "+f"(acc[i]) :: "memory");
      release(7, KIND == 0 ? rel_b : (KIND == 1 ? rel_ab : rel_b | (more & rel_ab)));
      PROF(t * 32 + wg * 16 + 2);
      if (t == 0) PROF_ST(30 + wg);

      auto pack = [&](int i, float off) {
        uint32_t v;
        asm("cvt.rn.bf16x2.f32 %0, %1, %2;" : "=r"(v) : "f"(acc[i * 2 + 1] - off), "f"(acc[i * 2] - off));
        return v;
      };
      auto cross = [&](int T, int i, float off) {
        uint32_t s2 = pack(T * 4 + i, off), o;
        asm("add.rn.bf16x2 %0, %1, %2;" : "=r"(s2) : "r"(s2), "r"(bq[T >> 1][(T & 1) * 2 + (i >> 1)]));
        asm("fma.rn.bf16x2 %0, %1, %2, %1;" : "=r"(o) : "r"(xr[T * 4 + i]), "r"(s2));
        return o;
      };
      auto reset = [&](int T) {
#pragma unroll
        for (int i = T * 8; i < T * 8 + 8; i += 4)
          asm volatile("ld.volatile.shared.v4.f32 {%0, %1, %2, %3}, [%4];"
                       : "+f"(acc[i]), "+f"(acc[i + 1]), "+f"(acc[i + 2]), "+f"(acc[i + 3]) : "r"(sb + OFF_INIT));
      };
      auto offset_for = [&](int T) { return T >= LAG ? acc[(T - LAG) * 8 + 7] : kOffset; };
      if (KIND == 2) {
        uint32_t id;
        asm volatile("mov.u32 %0, %%tid.x;" : "=r"(id));
        __nv_bfloat16* dst = optr + (size_t)(job_row(t) + wg * 64) * kDim + j * 256 + (id & 127) * 2;
        uint64_t pol;
        asm volatile("createpolicy.fractional.L2::evict_first.b64 %0, 1.0;" : "=l"(pol));
#pragma unroll
        for (int T = 0; T < 16; T++) {
#pragma unroll
          for (int i = 0; i < 4; i++)
            asm volatile("st.global.L2::cache_hint.b32 [%0], %1, %2;"
                         ::"l"(dst + (T * 4 + (i ^ 1)) * kDim), "r"(pack(T * 4 + i, offset_for(T))), "l"(pol) : "memory");
          reset(T);
        }
        asm volatile("bar.sync %0, 128;" ::"r"(wg + 1) : "memory");
        mbar_arrive_if(sb + BAR_PUB + wg * 8, rel_b);
      } else if (KIND == 1) {
#pragma unroll
        for (int T = 0; T < 16; T++) {
#pragma unroll
          for (int i = 0; i < 4; i++) xr[T * 4 + i] = cross(T, i, offset_for(T));
          if ((T & 1) && (T >> 1) + PRE < 8) load_bias((T >> 1) + PRE);
          reset(T);
        }
      } else {
#pragma unroll
        for (int T = 0; T < 16; T++) {
          uint32_t o[4];
#pragma unroll
          for (int i = 0; i < 4; i++) o[i] = cross(T, i, kOffset);
          stsm4((frag0 ^ ((T & 3) * 32)) + (T >> 2) * A_SLOT, o);
          if ((T & 3) == 3) chunk_staged(T >> 2);
          if ((T & 1) && (T >> 1) + PRE < 8) load_bias((T >> 1) + PRE);
        }
        PROF(t * 32 + wg * 16 + 7);
      }
      PROF(t * 32 + wg * 16 + 3);
    };

    PROF_ST(8);
    cluster_wait();
    PROF_ST(9);
    mbar_spin(sb + BAR_BFULL0, 0);
    PROF_ST(10);
    int t = 0;
#pragma unroll 1
    while (true) {
      if (t > 0) {
        if (helper) {
          epilogue(Int<2>(), t - 1, t < kJobs);
          if (t == kJobs) break;
        } else {
          epilogue(Int<1>(), t - 1, true);
        }
      }
      issue(0, 0, 0, false);
      if (t == 0) PROF_ST(11);
      l = 0;
      swap = t > 0 && !helper;
      brief = helper || t == short_t;
      hold = helper && t + 1 < kJobs;
      capture_q = (t > 0 || helper) ? -1 : j;
      PROF(t * 32 + wg * 16 + 0);
      k_loop(Flag<true>(), t);
      t++;
      if (helper) continue;
#pragma unroll 1
      do {
        epilogue(Int<0>(), t - 1, t < kTiles);
        if (t == kTiles) asm volatile("exit;");
        issue(0, 0, 0, false);
        l++;
        hold = l == kLayers - 1 && t + 1 < kTiles;
        PROF(t * 32 + wg * 16 + 0);
        k_loop(Flag<false>(), t);
        t++;
      } while (!hold);
    }
  }
}

__global__ void __launch_bounds__(256) dcn_fallback(const __nv_bfloat16* __restrict__ x0, const __nv_bfloat16* __restrict__ w,
                                                    const __nv_bfloat16* __restrict__ b, __nv_bfloat16* __restrict__ out) {
  __shared__ float xs[8][kDim];
  const size_t r0 = (size_t)blockIdx.x * 8;
  for (int i = threadIdx.x; i < 8 * kDim; i += 256) xs[i / kDim][i % kDim] = __bfloat162float(x0[r0 * kDim + i]);
  __syncthreads();
  for (int l = 0; l < kLayers; l++) {
    float a[4][8] = {};
    for (int k = 0; k < kDim; k++) {
#pragma unroll
      for (int c = 0; c < 4; c++) {
        const float wv = __bfloat162float(w[((size_t)l * kDim + k) * kDim + c * 256 + threadIdx.x]);
#pragma unroll
        for (int r = 0; r < 8; r++) a[c][r] += xs[r][k] * wv;
      }
    }
    __syncthreads();
#pragma unroll
    for (int c = 0; c < 4; c++) {
      const int n = c * 256 + threadIdx.x;
#pragma unroll
      for (int r = 0; r < 8; r++) {
        const float v = __bfloat162float(x0[(r0 + r) * kDim + n]) * (a[c][r] + __bfloat162float(b[l * kDim + n])) + xs[r][n];
        xs[r][n] = __bfloat162float(__float2bfloat16(v));
      }
    }
    __syncthreads();
  }
  for (int i = threadIdx.x; i < 8 * kDim; i += 256) out[r0 * kDim + i] = __float2bfloat16(xs[i / kDim][i % kDim]);
}

typedef CUresult (*EncodeFn)(CUtensorMap*, CUtensorMapDataType, cuuint32_t, void*, const cuuint64_t*, const cuuint64_t*,
                             const cuuint32_t*, const cuuint32_t*, CUtensorMapInterleave, CUtensorMapSwizzle,
                             CUtensorMapL2promotion, CUtensorMapFloatOOBfill);

static void make_map_2d(EncodeFn enc, CUtensorMap* m, void* ptr, uint64_t rows, uint32_t box_rows,
                        CUtensorMapSwizzle swizzle = CU_TENSOR_MAP_SWIZZLE_128B) {
  cuuint64_t dims[2] = {(cuuint64_t)kDim, rows};
  cuuint64_t strides[1] = {kDim * 2};
  cuuint32_t box[2] = {64, box_rows};
  cuuint32_t es[2] = {1, 1};
  enc(m, CU_TENSOR_MAP_DATA_TYPE_BFLOAT16, 2, ptr, dims, strides, box, es, CU_TENSOR_MAP_INTERLEAVE_NONE,
      swizzle, CU_TENSOR_MAP_L2_PROMOTION_L2_128B, CU_TENSOR_MAP_FLOAT_OOB_FILL_NONE);
}

}

extern "C" void kernel_launch(void* const* d_in, const int* in_sizes, int n_in, void* d_out, int out_size) {
  using namespace dcn;
  (void)in_sizes; (void)n_in; (void)out_size;
  void* fn = nullptr;
  cudaDriverEntryPointQueryResult qr;
  cudaGetDriverEntryPoint("cuTensorMapEncodeTiled", &fn, cudaEnableDefault, &qr);
  EncodeFn enc = (EncodeFn)fn;
  CUtensorMap mx64, mx32, mo64, mo32, mw, mp;
  make_map_2d(enc, &mx64, d_in[0], kRows, 64);
  make_map_2d(enc, &mx32, d_in[0], kRows, 32);
  make_map_2d(enc, &mo64, d_out, kRows, 64);
  make_map_2d(enc, &mo32, d_out, kRows, 32);
  make_map_2d(enc, &mp, d_out, kRows, 64, CU_TENSOR_MAP_SWIZZLE_NONE);
  {
    cuuint64_t dims[3] = {64, (cuuint64_t)kLayers * kDim, kDim / 64};
    cuuint64_t strides[2] = {kDim * 2, 128};
    cuuint32_t box[3] = {64, 32, 4};
    cuuint32_t es[3] = {1, 1, 1};
    enc(&mw, CU_TENSOR_MAP_DATA_TYPE_BFLOAT16, 3, d_in[1], dims, strides, box, es, CU_TENSOR_MAP_INTERLEAVE_NONE,
        CU_TENSOR_MAP_SWIZZLE_128B, CU_TENSOR_MAP_L2_PROMOTION_L2_128B, CU_TENSOR_MAP_FLOAT_OOB_FILL_NONE);
  }
  const __nv_bfloat16* x0 = (const __nv_bfloat16*)d_in[0];
  const __nv_bfloat16* w = (const __nv_bfloat16*)d_in[1];
  const __nv_bfloat16* b = (const __nv_bfloat16*)d_in[2];
  __nv_bfloat16* out = (__nv_bfloat16*)d_out;
  constexpr int smem = SMEM_BYTES + PROF_SMEM;
  cudaFuncSetAttribute(dcn_kernel, cudaFuncAttributeMaxDynamicSharedMemorySize, smem);

  cudaLaunchConfig_t cfg = {};
  cfg.gridDim = dim3(4 * kGroups + 4);
  cfg.blockDim = dim3(384);
  cfg.dynamicSmemBytes = smem;
  cudaLaunchAttribute attr;
  attr.id = cudaLaunchAttributeClusterDimension;
  attr.val.clusterDim.x = 2;
  attr.val.clusterDim.y = 1;
  attr.val.clusterDim.z = 1;
  cfg.attrs = &attr;
  cfg.numAttrs = 1;
  int clusters = 0;
  cudaOccupancyMaxActiveClusters(&clusters, dcn_kernel, &cfg);
  if (clusters >= 2 * kGroups) {
    const int grid = 4 * kGroups + (clusters >= 2 * kGroups + 2 ? 4 : 0);
    dcn_kernel<<<grid, 384, smem>>>(x0, w, b, out, mx64, mx32, mo64, mo32, mw, mp);
  } else {
    dcn_fallback<<<kRows / 8, 256>>>(x0, w, b, out);
  }
}
```

```cpp
#include <cuda_runtime.h>
#include <cuda.h>
#include <cuda_bf16.h>
#include <stdint.h>

namespace dcn {

__device__ __forceinline__ void wgmma_n256(float (&d)[128], uint64_t da, uint64_t db) {
  asm volatile("wgmma.mma_async.sync.aligned.m64n256k16.f32.bf16.bf16 "
    "{%0, %1, %2, %3, %4, %5, %6, %7, %8, %9, %10, %11, %12, %13, %14, %15, %16, %17, %18, %19, %20, %21, %22, %23, %24, %25, %26, %27, %28, %29, %30, %31, %32, %33, %34, %35, %36, %37, %38, %39, %40, %41, %42, %43, %44, %45, %46, %47, %48, %49, %50, %51, %52, %53, %54, %55, %56, %57, %58, %59, %60, %61, %62, %63, %64, %65, %66, %67, %68, %69, %70, %71, %72, %73, %74, %75, %76, %77, %78, %79, %80, %81, %82, %83, %84, %85, %86, %87, %88, %89, %90, %91, %92, %93, %94, %95, %96, %97, %98, %99, %100, %101, %102, %103, %104, %105, %106, %107, %108, %109, %110, %111, %112, %113, %114, %115, %116, %117, %118, %119, %120, %121, %122, %123, %124, %125, %126, %127}, "
    "%128, %129, 1, 1, 1, 0, 1;\n"
    : "+f"(d[0]), "+f"(d[1]), "+f"(d[2]), "+f"(d[3]), "+f"(d[4]), "+f"(d[5]), "+f"(d[6]), "+f"(d[7]), "+f"(d[8]), "+f"(d[9]), "+f"(d[10]), "+f"(d[11]), "+f"(d[12]), "+f"(d[13]), "+f"(d[14]), "+f"(d[15]), "+f"(d[16]), "+f"(d[17]), "+f"(d[18]), "+f"(d[19]), "+f"(d[20]), "+f"(d[21]), "+f"(d[22]), "+f"(d[23]), "+f"(d[24]), "+f"(d[25]), "+f"(d[26]), "+f"(d[27]), "+f"(d[28]), "+f"(d[29]), "+f"(d[30]), "+f"(d[31]), "+f"(d[32]), "+f"(d[33]), "+f"(d[34]), "+f"(d[35]), "+f"(d[36]), "+f"(d[37]), "+f"(d[38]), "+f"(d[39]), "+f"(d[40]), "+f"(d[41]), "+f"(d[42]), "+f"(d[43]), "+f"(d[44]), "+f"(d[45]), "+f"(d[46]), "+f"(d[47]), "+f"(d[48]), "+f"(d[49]), "+f"(d[50]), "+f"(d[51]), "+f"(d[52]), "+f"(d[53]), "+f"(d[54]), "+f"(d[55]), "+f"(d[56]), "+f"(d[57]), "+f"(d[58]), "+f"(d[59]), "+f"(d[60]), "+f"(d[61]), "+f"(d[62]), "+f"(d[63]), "+f"(d[64]), "+f"(d[65]), "+f"(d[66]), "+f"(d[67]), "+f"(d[68]), "+f"(d[69]), "+f"(d[70]), "+f"(d[71]), "+f"(d[72]), "+f"(d[73]), "+f"(d[74]), "+f"(d[75]), "+f"(d[76]), "+f"(d[77]), "+f"(d[78]), "+f"(d[79]), "+f"(d[80]), "+f"(d[81]), "+f"(d[82]), "+f"(d[83]), "+f"(d[84]), "+f"(d[85]), "+f"(d[86]), "+f"(d[87]), "+f"(d[88]), "+f"(d[89]), "+f"(d[90]), "+f"(d[91]), "+f"(d[92]), "+f"(d[93]), "+f"(d[94]), "+f"(d[95]), "+f"(d[96]), "+f"(d[97]), "+f"(d[98]), "+f"(d[99]), "+f"(d[100]), "+f"(d[101]), "+f"(d[102]), "+f"(d[103]), "+f"(d[104]), "+f"(d[105]), "+f"(d[106]), "+f"(d[107]), "+f"(d[108]), "+f"(d[109]), "+f"(d[110]), "+f"(d[111]), "+f"(d[112]), "+f"(d[113]), "+f"(d[114]), "+f"(d[115]), "+f"(d[116]), "+f"(d[117]), "+f"(d[118]), "+f"(d[119]), "+f"(d[120]), "+f"(d[121]), "+f"(d[122]), "+f"(d[123]), "+f"(d[124]), "+f"(d[125]), "+f"(d[126]), "+f"(d[127])
    : "l"(da), "l"(db));
}

constexpr int kDim = 1024;
constexpr int kRows = 16384;
constexpr int kLayers = 6;
constexpr int kGroups = 32;
constexpr int kRounds = kRows / 128 / kGroups;
constexpr int kTiles = kRounds * kLayers;

constexpr int kJobs = kGroups;
constexpr int kEpoch = 32;
constexpr int NA = 4;
constexpr int NB = 8;
constexpr float kOffset = 85.333336f;
constexpr float kTrunc = 64 * 0.375f / 131072;
constexpr int DRAIN = 1;
constexpr int LAG = 3;
constexpr int BPRE = 5;
constexpr int HPRE = 6;
constexpr uint32_t kAlign = 0x412a;
constexpr int NF = 2;
constexpr int A_SLOT = 8192;
constexpr int B_SLOT = 16384;
constexpr int OFF_B = 0;
constexpr int NP = 3;
constexpr int OFF_P = OFF_B + NB * B_SLOT;
constexpr int OFF_A = OFF_P + NP * A_SLOT;
constexpr int OFF_UNIT = OFF_A + 2 * NA * A_SLOT;
constexpr int OFF_BIAS = OFF_UNIT + 2048;
constexpr int OFF_INIT = OFF_BIAS + kLayers * 256 * 2;
constexpr int OFF_DELAY = OFF_INIT + 16;
constexpr int OFF_BAR = OFF_DELAY + 16;
constexpr int BAR_BFULL = OFF_BAR;
constexpr int BAR_BFULL0 = BAR_BFULL + NB * 8;
constexpr int BAR_BEMPTY = BAR_BFULL0 + NB * 8;
constexpr int BAR_AFULL = BAR_BEMPTY + NB * 8;
constexpr int BAR_AEMPTY = BAR_AFULL + 2 * NA * 8;
constexpr int BAR_XREADY = BAR_AEMPTY + 2 * NA * 8;
constexpr int BAR_PUB = BAR_XREADY + 16;
constexpr int BAR_PFULL = BAR_PUB + 16;
constexpr int BAR_PFREE = BAR_PFULL + 8 * 8;
constexpr int BAR_STAGED = BAR_PFREE + 8 * 8;
constexpr int BAR_ORDER = BAR_STAGED + 2 * NA * 8;
constexpr int BAR_BIAS = BAR_ORDER + 8;
constexpr int SMEM_BYTES = BAR_BIAS + 8;
static_assert(SMEM_BYTES <= 232448, "shared memory budget");

constexpr int kFlagSet = 4 * (kGroups + 1) * 32;
__device__ unsigned int g_flags[3 * kFlagSet];
__device__ unsigned long long g_phase[16 * 32];

__device__ __forceinline__ uint32_t smem_u32(const void* p) { return (uint32_t)__cvta_generic_to_shared(p); }
__device__ __forceinline__ void mbar_init(uint32_t bar, int cnt) {
  asm volatile("mbarrier.init.shared::cta.b64 [%0], %1;" ::"r"(bar), "r"(cnt) : "memory");
}
__device__ __forceinline__ void mbar_arrive(uint32_t bar) {
  asm volatile("mbarrier.arrive.shared::cta.b64 _, [%0];" ::"r"(bar) : "memory");
}
__device__ __forceinline__ uint32_t map_cta(uint32_t addr, uint32_t cta) {
  uint32_t r;
  asm volatile("mapa.shared::cluster.u32 %0, %1, %2;" : "=r"(r) : "r"(addr), "r"(cta));
  return r;
}
__device__ __forceinline__ void mbar_arrive_mapped_if(uint32_t cluster_addr, bool pred) {
  asm volatile("{\n.reg .pred p;\nsetp.ne.u32 p, %1, 0;\n@p mbarrier.arrive.shared::cluster.b64 _, [%0];\n}"
               ::"r"(cluster_addr), "r"((uint32_t)pred) : "memory");
}
__device__ __forceinline__ void mbar_arrive_if(uint32_t bar, bool pred) {
  asm volatile("{\n.reg .pred p;\nsetp.ne.u32 p, %1, 0;\n@p mbarrier.arrive.shared::cta.b64 _, [%0];\n}"
               ::"r"(bar), "r"((uint32_t)pred) : "memory");
}
__device__ __forceinline__ void mbar_wait(uint32_t bar, uint32_t parity) {
  asm volatile(
      "{\n.reg .pred p;\n.reg .u32 c;\n"
      "mbarrier.try_wait.parity.shared::cta.b64 p, [%0], %1;\n"
      "@p bra DONE;\n"
      "mov.u32 c, 0;\n"
      "LOOP:\n"
      "mbarrier.try_wait.parity.shared::cta.b64 p, [%0], %1;\n"
      "@p bra DONE;\n"
      "add.u32 c, c, 1;\n"
      "setp.lt.u32 p, c, 1048576;\n"
      "@p bra LOOP;\n"
      "trap;\n"
      "DONE:\n}"
      ::"r"(bar), "r"(parity) : "memory");
}
__device__ __forceinline__ bool mbar_watch(uint32_t bar, uint32_t parity, uint32_t later, uint32_t later_parity) {
  uint32_t seen;
  asm volatile(
      "{\n.reg .pred p;\n.reg .u32 c;\n"
      "mov.u32 %0, 0;\n"
      "mbarrier.test_wait.parity.shared::cta.b64 p, [%1], %2;\n"
      "@p bra DONE;\n"
      "mov.u32 c, 0;\n"
      "LOOP:\n"
      "mbarrier.try_wait.parity.shared::cta.b64 p, [%1], %2;\n"
      "selp.u32 %0, 1, 0, p;\n"
      "@p bra DONE;\n"
      "mbarrier.test_wait.parity.shared::cta.b64 p, [%3], %4;\n"
      "add.u32 c, c, 1;\n"
      "setp.ge.or.u32 p, c, 1048576, p;\n"
      "@!p bra LOOP;\n"
      "DONE:\n}"
      : "=r"(seen) : "r"(bar), "r"(parity), "r"(later), "r"(later_parity) : "memory");
  return __shfl_sync(0xffffffffu, seen, 0);
}
__device__ __forceinline__ void mbar_spin(uint32_t bar, uint32_t parity) {
  asm volatile(
      "{\n.reg .pred p;\n"
      "LOOP:\n"
      "mbarrier.try_wait.parity.shared::cta.b64 p, [%0], %1;\n"
      "@!p bra LOOP;\n}"
      ::"r"(bar), "r"(parity) : "memory");
}
#define ELECT_BEGIN "{\n.reg .pred e;\nelect.sync _|e, 0xffffffff;\n"
template <bool STREAM> __device__ __forceinline__ void expect_load_2d_e(uint32_t dst, const CUtensorMap* m, uint32_t bar, int c0, int c1) {
  if (STREAM) {
    asm volatile(ELECT_BEGIN ".reg .b64 pol;\ncreatepolicy.fractional.L2::evict_first.b64 pol, 1.0;\n"
                 "@e mbarrier.arrive.expect_tx.shared::cta.b64 _, [%2], 8192;\n"
                 "@e cp.async.bulk.tensor.2d.shared::cluster.global.mbarrier::complete_tx::bytes.L2::cache_hint [%0], [%1, {%3, %4}], [%2], pol;\n}"
                 ::"r"(dst), "l"(m), "r"(bar), "r"(c0), "r"(c1) : "memory");
  } else {
    asm volatile(ELECT_BEGIN
                 "@e mbarrier.arrive.expect_tx.shared::cta.b64 _, [%2], 8192;\n"
                 "@e cp.async.bulk.tensor.2d.shared::cluster.global.mbarrier::complete_tx::bytes [%0], [%1, {%3, %4}], [%2];\n}"
                 ::"r"(dst), "l"(m), "r"(bar), "r"(c0), "r"(c1) : "memory");
  }
}
__device__ __forceinline__ void expect_load_2d_mc_e(uint32_t dst, const CUtensorMap* m, uint32_t bar, int c0, int c1) {
  asm volatile(ELECT_BEGIN ".reg .b64 pol;\ncreatepolicy.fractional.L2::evict_first.b64 pol, 1.0;\n"
               "@e mbarrier.arrive.expect_tx.shared::cta.b64 _, [%2], 8192;\n"
               "@e cp.async.bulk.tensor.2d.shared::cluster.global.mbarrier::complete_tx::bytes.multicast::cluster.L2::cache_hint [%0], [%1, {%3, %4}], [%2], %5, pol;\n}"
               ::"r"(dst), "l"(m), "r"(bar), "r"(c0), "r"(c1), "h"((uint16_t)3) : "memory");
}
__device__ __forceinline__ void expect_load_3d_e(uint32_t dst, const CUtensorMap* m, uint32_t bar, int c0, int c1, int c2) {
  asm volatile(ELECT_BEGIN
               "@e mbarrier.arrive.expect_tx.shared::cta.b64 _, [%2], 16384;\n"
               "@e cp.async.bulk.tensor.3d.shared::cluster.global.mbarrier::complete_tx::bytes [%0], [%1, {%3, %4, %5}], [%2];\n}"
               ::"r"(dst), "l"(m), "r"(bar), "r"(c0), "r"(c1), "r"(c2) : "memory");
}
template <bool STREAM> __device__ __forceinline__ void store_2d_e(const CUtensorMap* m, uint32_t src, int c0, int c1) {
  if (STREAM) {
    asm volatile(ELECT_BEGIN ".reg .b64 pol;\ncreatepolicy.fractional.L2::evict_first.b64 pol, 1.0;\n"
                 "@e cp.async.bulk.tensor.2d.global.shared::cta.bulk_group.L2::cache_hint [%0, {%2, %3}], [%1], pol;\n}"
                 ::"l"(m), "r"(src), "r"(c0), "r"(c1) : "memory");
  } else {
    asm volatile(ELECT_BEGIN
                 "@e cp.async.bulk.tensor.2d.global.shared::cta.bulk_group [%0, {%2, %3}], [%1];\n}"
                 ::"l"(m), "r"(src), "r"(c0), "r"(c1) : "memory");
  }
}
__device__ __forceinline__ void prefetch_2d_e(const CUtensorMap* m, int c0, int c1) {
  asm volatile(ELECT_BEGIN
               "@e cp.async.bulk.prefetch.tensor.2d.L2.global [%0, {%1, %2}];\n}"
               ::"l"(m), "r"(c0), "r"(c1) : "memory");
}
__device__ __forceinline__ void prefetch_1d_e(const void* ptr, uint32_t bytes) {
  asm volatile(ELECT_BEGIN
               "@e cp.async.bulk.prefetch.L2.global [%0], %1;\n}"
               ::"l"(ptr), "r"(bytes) : "memory");
}
__device__ __forceinline__ void paced_load_3d_e(uint32_t dst, const CUtensorMap* m, uint32_t bar, int c0, int c1, int c2, bool pace) {
  asm volatile(ELECT_BEGIN ".reg .pred p;\nsetp.ne.u32 p, %6, 0;\n"
               "@e mbarrier.arrive.expect_tx.shared::cta.b64 _, [%2], 16384;\n"
               "@p nanosleep.u32 128;\n"
               "@e cp.async.bulk.tensor.3d.shared::cluster.global.mbarrier::complete_tx::bytes [%0], [%1, {%3, %4, %5}], [%2];\n}"
               ::"r"(dst), "l"(m), "r"(bar), "r"(c0), "r"(c1), "r"(c2), "r"((uint32_t)pace) : "memory");
}
__device__ __forceinline__ void arrive_mapped_e(uint32_t cluster_addr) {
  asm volatile(ELECT_BEGIN "@e mbarrier.arrive.shared::cluster.b64 _, [%0];\n}" ::"r"(cluster_addr) : "memory");
}
__device__ __forceinline__ void arrive_e(uint32_t bar) {
  asm volatile(ELECT_BEGIN "@e mbarrier.arrive.shared::cta.b64 _, [%0];\n}" ::"r"(bar) : "memory");
}
__device__ __forceinline__ void bulk_commit() { asm volatile("cp.async.bulk.commit_group;" ::: "memory"); }
template <int N> __device__ __forceinline__ void bulk_wait() { asm volatile("cp.async.bulk.wait_group %0;" ::"n"(N) : "memory"); }
__device__ __forceinline__ void wg_fence() { asm volatile("wgmma.fence.sync.aligned;" ::: "memory"); }
__device__ __forceinline__ void wg_commit() { asm volatile("wgmma.commit_group.sync.aligned;" ::: "memory"); }
template <int N> __device__ __forceinline__ void wg_wait() { asm volatile("wgmma.wait_group.sync.aligned %0;" ::"n"(N) : "memory"); }
__device__ __forceinline__ void fence_async_global() { asm volatile("fence.proxy.async.global;" ::: "memory"); }
__device__ __forceinline__ void st_relaxed(unsigned int* p, unsigned int v) {
  asm volatile("st.relaxed.gpu.global.u32 [%0], %1;" ::"l"(p), "r"(v) : "memory");
}
__device__ __forceinline__ void ldsm4(uint32_t* r, uint32_t addr) {
  asm volatile("ldmatrix.sync.aligned.m8n8.x4.shared.b16 {%0, %1, %2, %3}, [%4];"
               : "=r"(r[0]), "=r"(r[1]), "=r"(r[2]), "=r"(r[3]) : "r"(addr) : "memory");
}
__device__ __forceinline__ void stsm4(uint32_t addr, const uint32_t* r) {
  asm volatile("stmatrix.sync.aligned.m8n8.x4.shared.b16 [%0], {%1, %2, %3, %4};"
               ::"r"(addr), "r"(r[0]), "r"(r[1]), "r"(r[2]), "r"(r[3]) : "memory");
}
template <bool V> struct Flag { static constexpr bool value = V; };
template <int V> struct Int { static constexpr int value = V; };
__device__ __forceinline__ void fence_async_smem() { asm volatile("fence.proxy.async.shared::cta;" ::: "memory"); }
__device__ __forceinline__ void cluster_arrive_relaxed() { asm volatile("barrier.cluster.arrive.relaxed.aligned;" ::: "memory"); }
__device__ __forceinline__ void cluster_wait() { asm volatile("barrier.cluster.wait.acquire.aligned;" ::: "memory"); }
__device__ __forceinline__ void prefetch_map(const CUtensorMap* m) {
  asm volatile("prefetch.tensormap [%0];" ::"l"(m) : "memory");
}
__device__ __forceinline__ void prefetch_map_e(const CUtensorMap* m) {
  asm volatile(ELECT_BEGIN "@e prefetch.tensormap [%0];\n}" ::"l"(m) : "memory");
}
__device__ __forceinline__ void poll_flag(const unsigned int* ptr, unsigned int target) {
  asm volatile(
      "{\n.reg .pred p;\n.reg .u32 c;\n.reg .s32 v;\n"
      "mov.u32 c, 0;\n"
      "LOOP:\n"
      "ld.acquire.gpu.global.s32 v, [%0];\n"
      "sub.s32 v, v, %1;\n"
      "setp.ge.s32 p, v, 0;\n"
      "@p bra DONE;\n"
      "add.u32 c, c, 1;\n"
      "setp.lt.u32 p, c, 1048576;\n"
      "@p bra LOOP;\n"
      "trap;\n"
      "DONE:\n}"
      ::"l"(ptr), "r"(target) : "memory");
}

constexpr uint32_t DESC_HI = (1024u >> 4) | (1u << 30);
__device__ __forceinline__ uint64_t desc(uint32_t lo) { return ((uint64_t)DESC_HI << 32) | lo; }
constexpr uint32_t DESC_A_LBO = 1u << 16;
constexpr uint32_t DESC_B_LBO = (4096u >> 4) << 16;

__device__ __forceinline__ int kgroup_col(int j, int q) {
  return q == 0 ? j : (q == 1 ? (j ^ 1) : (((j ^ 2) & ~1) + (q - 2)));
}

__device__ __forceinline__ int role_of_cluster(int c) {
  const int a = c - 4;
  const int b = c - 36, r = (b * 37) >> 8;
  const int first = (a & ~7) + (a & 3) * 2 + ((a >> 2) & 1);
  const int second = 32 + r * 8 + ((0x7531640 >> (((b - r * 7) * 4) & 31)) & 7);
  return c >= 2 * kGroups ? c : (c >= 36 ? second : (c >= 4 ? first : 34 + c * 8));
}
__device__ __forceinline__ int helped_round(int grp) { return (grp & 2) ? (grp & 3) - 1 : 3; }
__device__ __forceinline__ int job_of_group(int grp) {
  return (grp & 2) ? (grp & 1) * 8 + (grp >> 2) : 16 + (grp >> 2) * 2 + (grp & 1);
}
__device__ __forceinline__ int job_row(int n) {
  const int grp = n < 16 ? (n & 7) * 4 + 2 + (n >> 3) : ((n - 16) >> 1) * 4 + (n & 1);
  return (helped_round(grp) * kGroups + grp) * 128;
}

constexpr int PROF_SMEM = 0;
#define PROF_BOTH(idx) do {} while (0)
#define PROF_SVC(idx) do {} while (0)
#define PROF_DUMP() do {} while (0)
#define PROF(idx) do {} while (0)
#define PROF_ST(idx) do {} while (0)
#define PROF_SKEW(idx) do {} while (0)

__global__ void __cluster_dims__(2, 1, 1) __launch_bounds__(384, 1)
dcn_kernel(const __nv_bfloat16* __restrict__ xptr, const __nv_bfloat16* __restrict__ wptr,
           const __nv_bfloat16* __restrict__ bias, __nv_bfloat16* optr,
           const __grid_constant__ CUtensorMap mx64, const __grid_constant__ CUtensorMap mx32,
           const __grid_constant__ CUtensorMap mo64, const __grid_constant__ CUtensorMap mo32,
           const __grid_constant__ CUtensorMap mw, const __grid_constant__ CUtensorMap mp) {
  extern __shared__ __align__(1024) uint8_t smem_raw[];
  const uint32_t sb = smem_u32(smem_raw);
  const int tid = threadIdx.x;
  if ((tid >> 5) == 8) PROF_ST(0);
  if ((tid >> 5) == 9) PROF_BOTH(48);
  const int wid = __shfl_sync(0xffffffffu, tid >> 5, 0);
  if (wid == 0) {
    asm volatile("prefetch.global.L2 [%0];" ::"l"(wptr + ((blockIdx.x & 31) * 32 + tid) * 64));
    asm volatile("prefetch.global.L2 [%0];" ::"l"(xptr + ((blockIdx.x & 127) * 32 + tid) * kDim));
    prefetch_map_e(&mw);
    prefetch_map_e(&mx64);
    PROF_ST(29);
  }
  const int bid = role_of_cluster(blockIdx.x >> 1) * 2 + (blockIdx.x & 1);
  const int j = bid & 3;
  const int grp = bid >> 2;
  const bool helper = grp == kGroups;
  const int col0 = helper ? kgroup_col(j, 2) * 256 : 0;
  const int row0 = helper ? job_row(0) : grp * 128;
  auto first_loads = [&](int s) {
    const int col = col0 + s * 64;
    expect_load_3d_e(sb + OFF_B + 2 * s * B_SLOT, &mw, sb + BAR_BFULL0 + 2 * s * 8, 0, col, j * 4);
    expect_load_2d_e<false>(sb + OFF_A + s * A_SLOT, &mx64, sb + BAR_AFULL + s * 8, col, row0);
    expect_load_3d_e(sb + OFF_B + (2 * s + 1) * B_SLOT, &mw, sb + BAR_BFULL0 + (2 * s + 1) * 8, 0, col + 32, j * 4);
    expect_load_2d_e<false>(sb + OFF_A + (NA + s) * A_SLOT, &mx64, sb + BAR_AFULL + (NA + s) * 8, col, row0 + 64);
    PROF_ST(2 + s);
  };
  auto init_full = [&](int s) {
    mbar_init(sb + BAR_BFULL0 + 2 * s * 8, 1);
    mbar_init(sb + BAR_BFULL0 + (2 * s + 1) * 8, 1);
    mbar_init(sb + BAR_AFULL + s * 8, 1);
    mbar_init(sb + BAR_AFULL + (NA + s) * 8, 1);
  };
  if (wid == 8) {
    PROF_ST(28);
    if (tid == 256) {
      init_full(0);
      asm volatile("fence.mbarrier_init.release.cluster;" ::: "memory");
    }
    __syncwarp();
    PROF_ST(1);
    first_loads(0);
    if (tid == 256) {
#pragma unroll
      for (int s = 1; s < 4; s++) init_full(s);
      asm volatile("fence.mbarrier_init.release.cluster;" ::: "memory");
    }
    __syncwarp();
#pragma unroll
    for (int s = 1; s < NF; s++) first_loads(s);
  }
  const int wg = wid >> 2;
  const int warp = wid & 3;
  const uint32_t rank = j & 1;
  const int short_t = (gridDim.x > 4 * kGroups && !helper) ? helped_round(grp) * kLayers : -8;
  const unsigned lend = helper ? ~0u : 1u;
  auto moves_up = [&](int t) { return (unsigned)(t + 1 - short_t) > lend; };

  if (wg == 2) {
    asm volatile("setmaxnreg.dec.sync.aligned.u32 40;");
    if (tid == 288) {
      if (sb & 1023) asm volatile("trap;");
#pragma unroll
      for (int i = 0; i < NB; i++) { mbar_init(sb + BAR_BFULL + i * 8, 1); mbar_init(sb + BAR_BEMPTY + i * 8, 2); }
#pragma unroll
      for (int i = 0; i < 4; i++) mbar_init(sb + BAR_XREADY + i * 8, 1);
      mbar_init(sb + BAR_ORDER, 1);
    } else if (tid == 320) {
#pragma unroll
      for (int i = 0; i < 2 * NA; i++) { mbar_init(sb + BAR_AEMPTY + i * 8, 2); mbar_init(sb + BAR_STAGED + i * 8, 4); }
    } else if (tid == 352) {
#pragma unroll
      for (int i = 0; i < 8; i++) { mbar_init(sb + BAR_PFULL + i * 8, 1); mbar_init(sb + BAR_PFREE + i * 8, 1); }
      mbar_init(sb + BAR_BIAS, 32);
      asm volatile("st.shared.v4.f32 [%0], {%1, %1, %1, %1};" ::"r"(sb + OFF_INIT), "f"(kOffset) : "memory");
      asm volatile("st.shared.v2.u32 [%0], {0, 0};" ::"r"(sb + OFF_DELAY) : "memory");
    }
    asm volatile("fence.mbarrier_init.release.cluster;" ::: "memory");
    __syncwarp();
    cluster_arrive_relaxed();
    if (warp == 0) {
      PROF_ST(6);
#pragma unroll 1
      for (int s = NF; s < 4; s++) first_loads(s);
      cluster_wait();
      PROF_ST(7);
      uint32_t par = 0;
      int l = 0;
      const int ntiles = helper ? kJobs : kTiles;
#pragma unroll 1
      for (int t = 0; t < ntiles; t++) {
        const int jo = (t == 0 && !helper) ? 0 : j;
        const int q_end = t == short_t ? 2 : 4;
#pragma unroll 1
        for (int q = (helper ? 2 : 0) + (t == 0); q < q_end; q++) {
          const int krow = l * kDim + kgroup_col(jo, q) * 256;
          const bool first = q == (helper ? 2 : 0);
          const bool up = q >= 2 && moves_up(t);
          const int shift = first ? (moves_up(t - 1) ? -1 : 0) : (up && q == 2 ? 1 : 0);
          const int paced = first ? (shift ? DRAIN + 1 : 0) : ((helper || (q == 1 && (t == short_t || t == 0))) ? 0 : NB);
          const uint32_t dst = sb + OFF_B + (up ? B_SLOT : 0);
          const uint32_t full = sb + (first ? BAR_BFULL0 : BAR_BFULL);
          if (shift > 0) mbar_spin(sb + BAR_BEMPTY, par);
#pragma unroll 1
          for (int i = 0; i < NB; i++) {
            if ((unsigned)(i + shift) < NB) mbar_spin(sb + BAR_BEMPTY + (i + shift) * 8, par);
            paced_load_3d_e(dst + i * B_SLOT, &mw, full + i * 8, 0, krow + i * 32, j * 4, i < paced);
            PROF_SKEW(t * 32 + q * 8 + i);
          }
          if (shift < 0) mbar_spin(sb + BAR_BEMPTY + (NB - 1) * 8, par);
          par ^= 1;
        }
        if (helper || ++l == kLayers) l = 0;
      }
    } else if (warp <= 2) {
      const int w = warp - 1;
      const uint32_t abase = sb + OFF_A + w * NA * A_SLOT;
      const uint32_t fullb = sb + BAR_AFULL + w * NA * 8;
      const uint32_t emptyb = sb + BAR_AEMPTY + w * 8;
      const uint32_t stagedb = sb + BAR_STAGED + w * NA * 8;
      const unsigned int base = __shfl_sync(0xffffffffu, *(volatile unsigned int*)(g_flags + bid * 32), 0);
      cluster_wait();
      uint32_t epar = 0;
      uint32_t spar = 0;
      auto refill = [&](const CUtensorMap* m, int col, int row) {
#pragma unroll 1
        for (int s = 0; s < 4; s++) {
          mbar_spin(emptyb + s * 16, epar);
          expect_load_2d_e<false>(abase + s * A_SLOT, m, fullb + s * 8, col + s * 64, row);
        }
        epar ^= 1;
      };
      auto store_refill = [&](int out_row, int col, int row, bool last_read) {
#pragma unroll 1
        for (int s = 0; s < 4; s++) {
          mbar_spin(stagedb + s * 8, spar);
          fence_async_smem();
          store_2d_e<true>(&mo64, abase + s * A_SLOT, j * 256 + s * 64, out_row);
          bulk_commit();
          bulk_wait<0>();
          __syncwarp();
          mbar_spin(emptyb + s * 16, epar);
          if (last_read) expect_load_2d_e<true>(abase + s * A_SLOT, &mx64, fullb + s * 8, col + s * 64, row);
          else expect_load_2d_e<false>(abase + s * A_SLOT, &mx64, fullb + s * 8, col + s * 64, row);
        }
        spar ^= 1;
        epar ^= 1;
      };
      auto store_tile = [&](auto stream, int out_row) {
#pragma unroll 1
        for (int c = 0; c < 4; c++) {
          mbar_spin(stagedb + c * 8, spar);
          fence_async_smem();
          arrive_e(fullb + c * 8);
          if (!decltype(stream)::value && w == 1) {
            bulk_commit();
            bulk_wait<0>();
          }
          store_2d_e<decltype(stream)::value>(&mo64, abase + c * A_SLOT, j * 256 + c * 64, out_row);
        }
        spar ^= 1;
        bulk_commit();
        bulk_wait<0>();
        __syncwarp();
      };
      auto refill_shared = [&](const CUtensorMap* m32, int col, int row) {
#pragma unroll 1
        for (int s = 0; s < 4; s++) {
          mbar_spin(emptyb + s * 16, epar);
          expect_load_2d_mc_e(abase + s * A_SLOT + rank * 4096, m32, fullb + s * 8, col + s * 64, row + rank * 32);
        }
        epar ^= 1;
      };
      if (helper) {
#pragma unroll 1
        for (int h = 1; h < 2 * kJobs; h++) refill_shared(&mx32, col0 + (h & 1) * 256, job_row(h >> 1) + w * 64);
      } else {
        const uint32_t xready_peer = map_cta(sb + BAR_XREADY + w * 8, rank ^ 1);
        const unsigned int* oflag = g_flags + (grp * 4 + kgroup_col(j, 2)) * 32;
        unsigned int* done_mine = g_flags + kFlagSet + (bid * 2 + w) * 32;
        const unsigned int* done_peer = g_flags + kFlagSet + ((bid ^ 2) * 2 + w) * 32;
        uint32_t nx = 0;
#pragma unroll 1
        for (int rd = 0; rd < kRounds; rd++) {
          const int xrow = (rd * kGroups + grp) * 128 + w * 64;
          if (rd == 0) {
            refill(&mx64, 256, xrow);
          } else {
            poll_flag(done_peer, base + nx);
            store_refill(xrow - kGroups * 128, (j ^ 1) * 256, xrow, rd * kLayers == short_t);
          }
          if (rd * kLayers != short_t) {
#pragma unroll 1
            for (int h = 0; h < 2; h++) refill_shared(&mx32, (kgroup_col(rd == 0 ? 0 : j, 2) + h) * 256, xrow);
          }
#pragma unroll 1
          for (int l = 1; l < kLayers; l++) {
            if (l > 1) poll_flag(done_peer, base + nx);
            store_tile(Flag<false>(), xrow);
            PROF_SVC((rd * kLayers + l - 1) * 2 + w);
            arrive_mapped_e(xready_peer);
            arrive_e(sb + BAR_PUB + w * 8);
            mbar_spin(sb + BAR_XREADY + w * 8, nx & 1);
            fence_async_global();
            refill(&mo64, (j ^ 1) * 256, xrow);
#pragma unroll 1
            for (int h = 0; h < 2; h++) {
              poll_flag(oflag + h * 32, base + nx + 1);
              fence_async_global();
              refill_shared(&mo32, (kgroup_col(j, 2) + h) * 256, xrow);
            }
            if (rank) {
#pragma unroll 1
              for (int s = 0; s < 4; s++) mbar_spin(fullb + s * 8, 1);
            }
            nx++;
            if ((tid & 31) == 0) st_relaxed(done_mine, base + (nx == kRounds * (kLayers - 1) ? kEpoch : nx));
            __syncwarp();
          }
          const int nrow = xrow + kGroups * 128;
          if (rd + 1 == kRounds) {
            poll_flag(done_peer, base + nx);
            store_tile(Flag<true>(), xrow);
            PROF_SVC((rd * kLayers + kLayers - 1) * 2 + w);
            arrive_e(sb + BAR_PUB + w * 8);
          } else {
            refill(&mx64, j * 256, nrow);
            PROF_SVC((rd * kLayers + kLayers - 1) * 2 + w);
          }
        }
      }
    } else {
      const int lane = tid & 31;
      unsigned int* myflag = g_flags + bid * 32;
      if (lane == 0) { prefetch_map(&mx32); prefetch_map(&mo64); prefetch_map(&mo32); }
      const unsigned int base = *(volatile unsigned int*)myflag;
      auto publish = [&](uint32_t n, uint32_t value) {
#pragma unroll 1
        for (int w = 0; w < 2; w++) mbar_wait(sb + BAR_PUB + w * 8, n & 1);
        if (lane == 0) asm volatile("st.release.gpu.global.u32 [%0], %1;" ::"l"(myflag), "r"(base + value) : "memory");
        __syncwarp();
      };
      if (helper) {
        mbar_arrive(sb + BAR_BIAS);
        cluster_wait();
#pragma unroll 1
        for (int n = 0; n < kJobs; n++) {
          if (n + 2 < kJobs) {
            const int row = job_row(n + 2);
#pragma unroll 1
            for (int i = 0; i < 8; i++) prefetch_2d_e(&mx64, col0 + rank * 256 + (i & 3) * 64, row + (i >> 2) * 64);
          }
          publish(n, n + 1);
        }
      } else {
        {
          float c[8];
#pragma unroll
          for (int i = 0; i < 8; i++) c[i] = 0.f;
#pragma unroll 1
          for (int l = 0; l < kLayers; l++) {
            const uint4 v = *reinterpret_cast<const uint4*>(bias + l * kDim + j * 256 + lane * 8);
            const uint32_t u[4] = {v.x, v.y, v.z, v.w};
#pragma unroll
            for (int i = 0; i < 4; i++) {
              c[2 * i] += __uint_as_float(u[i] << 16) + kTrunc;
              c[2 * i + 1] += __uint_as_float(u[i] & 0xffff0000u) + kTrunc;
              uint32_t pk;
              asm("cvt.rn.bf16x2.f32 %0, %1, %2;" : "=r"(pk) : "f"(c[2 * i + 1]), "f"(c[2 * i]));
              asm volatile("st.shared.u32 [%0], %1;" ::"r"(sb + OFF_BIAS + l * 512 + (lane >> 2) * 64 + i * 16 + (lane & 3) * 4),
                           "r"(pk) : "memory");
            }
          }
#pragma unroll
          for (int i = 0; i < 15; i++) {
            const uint32_t one = (lane >> 3) == (lane & 3) ? 0x3f80u << ((lane & 4) * 4) : 0u;
            asm volatile("st.shared.u32 [%0], %1;" ::"r"(sb + OFF_UNIT + i * 128 + lane * 4), "r"(i == 7 ? one : 0u) : "memory");
          }
          fence_async_smem();
          mbar_arrive(sb + BAR_BIAS);
        }
        const __nv_bfloat16* wslice = wptr + bid * 8192;
        cluster_wait();
        prefetch_1d_e(wslice + kDim * kDim, 16384);
        uint32_t nx = 0;
#pragma unroll 1
        for (int rd = 0; rd < kRounds; rd++) {
#pragma unroll 1
          for (int l = 1; l < kLayers; l++) {
            const int t = rd * kLayers + l;
            const bool align = ((kAlign >> t) & 1) &&
                               mbar_watch(sb + BAR_STAGED + NA * 8, (t - 1) & 1, sb + BAR_PUB + 8, nx & 1);
            unsigned long long mine = 0;
            uint32_t tick = 0;
            if (align) {
              uint32_t c0, c1;
              asm volatile("mov.u32 %0, %%clock;\nnanosleep.u32 128;\nmov.u32 %1, %%clock;\nmov.u64 %2, %%globaltimer;\n"
                           "nanosleep.u32 128;\nmov.u32 %3, %%clock;"
                           : "=r"(c0), "=r"(c1), "=l"(mine), "=r"(tick) :: "memory");
              tick -= c1;
              mine = ((mine + 64) >> 8 << 10) - (c1 - c0);
            }
            publish(nx, nx + 1 == kRounds * (kLayers - 1) ? kEpoch : nx + 1);
            nx++;
            {
              uint32_t delay = 0;
              if (align) {
                unsigned long long* word = g_phase + (bid & 15) * 32 + t;
                if (lane == 0) atomicMax(word, mine);
                __syncwarp();
#pragma unroll 1
                for (int i = 0; i < 3; i++) __nanosleep(256);
                unsigned long long latest;
                asm volatile("ld.relaxed.gpu.global.u64 %0, [%1];" : "=l"(latest) : "l"(word) : "memory");
                const uint32_t a = (uint32_t)latest, b = (uint32_t)mine;
                const int lag = (int)(((a + 1023) >> 10) - ((b + 1023) >> 10)) * (int)tick - (int)((-a & 1023) - (-b & 1023));
                delay = (lag > 40 && lag < 700) ? lag + 280 : 0;
              }
              asm volatile("st.relaxed.cta.shared.u32 [%0], %1;" ::"r"(sb + OFF_DELAY), "r"(delay) : "memory");
            }
            if (l < kLayers - 1 && rd == 0) prefetch_1d_e(wslice + (l + 1) * kDim * kDim, 16384);
            if (l > 1 && rd + 1 < kRounds) {
              const int nrow = ((rd + 1) * kGroups + grp) * 128;
              prefetch_1d_e(xptr + (size_t)(nrow + j * 32 + l * 8 - 16) * kDim, 8192);
              __nanosleep(600);
              prefetch_1d_e(xptr + (size_t)(nrow + j * 32 + l * 8 - 12) * kDim, 8192);
              if (rd * kLayers + l + 1 == short_t) {
                poll_flag(g_flags + (4 * kGroups + j) * 32, base + job_of_group(grp) + 1);
                fence_async_global();
                constexpr uint32_t order = 0x76325140;
#pragma unroll 1
                for (int i = NP; i < 8; i++)
                  prefetch_2d_e(&mp, j * 256 + ((order >> (i * 4)) & 3) * 64, nrow + ((order >> (i * 4)) & 4) * 16);
#pragma unroll 1
                for (int i = 0; i < 8; i++) {
                  if (i >= NP) mbar_wait(sb + BAR_PFREE + (i - NP) * 8, 0);
                  PROF(776 + i);
                  expect_load_2d_e<true>(sb + OFF_P + (i % NP) * A_SLOT, &mp, sb + BAR_PFULL + i * 8,
                                         j * 256 + ((order >> (i * 4)) & 3) * 64, nrow + ((order >> (i * 4)) & 4) * 16);
                }
              }
            }
          }
        }
#pragma unroll 1
        for (int w = 0; w < 2; w++) mbar_wait(sb + BAR_PUB + w * 8, nx & 1);
      }
    }
    if (warp == 3) PROF_DUMP();
  } else {
    cluster_arrive_relaxed();
    asm volatile("setmaxnreg.inc.sync.aligned.u32 232;");
    PROF_ST(32);
    const int lane = tid & 31;
    const int wtid = tid & 127;
    const uint32_t abase = sb + OFF_A + wg * NA * A_SLOT;
    const uint32_t afull = sb + BAR_AFULL + wg * NA * 8;
    const uint32_t rel = map_cta(sb + (wtid == 64 ? BAR_BEMPTY : BAR_AEMPTY + wg * 8 - 8), wtid == 32 ? (rank ^ 1) : rank);
    const bool rel_b = wtid == 64;
    const bool rel_ab = (wtid & 31) == 0 && wtid < 96;
    const uint32_t frag0 = __shfl_sync(0xffffffffu, abase + ((wtid >> 5) * 16 + ((lane >> 3) & 1) * 8 + (lane & 7)) * 128 +
                                                        (((lane >> 4) ^ (lane & 7)) << 4), lane);
    const uint64_t adesc0 = desc(((abase & 0x3FFFF) >> 4) | DESC_A_LBO);
    const uint64_t bdesc0 = desc((((sb + OFF_B) & 0x3FFFF) >> 4) | DESC_B_LBO);

    const uint64_t zero = gridDim.y - 1;
    uint64_t adesc_q = adesc0 + zero, bdesc_q = bdesc0 + zero;

    float acc[128];
    uint32_t xr[64];
#pragma unroll
    for (int i = 0; i < 128; i++) acc[i] = kOffset;
#pragma unroll
    for (int i = 0; i < 64; i++) xr[i] = 0;
    int l = 0;
    bool hold = false;
    bool swap = false;
    bool brief = helper;
    int capture_q = helper ? -1 : j;

    auto release = [&](int i, bool with_a) {
      mbar_arrive_mapped_if(rel + i * 8, (i & 1) ? with_a : rel_b);
    };
    auto chunk_staged = [&](int c) {
      __syncwarp();
      arrive_e(sb + BAR_STAGED + (wg * NA + c) * 8);
    };
    auto capture_slot = [&](int p) {
#pragma unroll
      for (int g = 0; g < 4; g++) ldsm4(&xr[(p * 4 + g) * 4], (frag0 ^ (g * 32)) + p * A_SLOT);
    };
    auto swap_half = [&](int p, int half) {
#pragma unroll
      for (int g = half * 2; g < half * 2 + 2; g++) {
        const uint32_t addr = (frag0 ^ (g * 32)) + p * A_SLOT;
        uint32_t n[4];
        ldsm4(n, addr);
        stsm4(addr, &xr[(p * 4 + g) * 4]);
#pragma unroll
        for (int i = 0; i < 4; i++) xr[(p * 4 + g) * 4 + i] = n[i];
      }
      if (half) chunk_staged(p);
    };
    auto chunk_of = [&](int c) { return wg ? (0x7631 >> (c * 4)) & 7 : (0x5420 >> (c * 4)) & 7; };
    auto add_partial = [&](int c) __attribute__((always_inline)) {
      const int n = chunk_of(c);
      const int slot = wg ? (0x1001 >> (c * 4)) & 3 : (0x2120 >> (c * 4)) & 3;
      PROF(768 + wg * 16 + c * 2);
      mbar_spin(sb + BAR_PFULL + n * 8, 0);
      PROF(768 + wg * 16 + c * 2 + 1);
      wg_fence();
      wgmma_n256(acc, ((uint64_t)(128 >> 4) << 32) | ((128 >> 4) << 16) | (((sb + OFF_UNIT + (6 - 2 * c) * 128) & 0x3FFFF) >> 4),
                 ((uint64_t)(256 >> 4) << 32) | ((128 >> 4) << 16) | (((sb + OFF_P + slot * A_SLOT) & 0x3FFFF) >> 4));
    };
    auto issue = [&](int i, int q, int t, bool wait_b) __attribute__((always_inline)) {
      if (!(i & 1)) mbar_spin(afull + (i >> 1) * 8, q & 1);
      if (wait_b) mbar_spin(sb + (q ? BAR_BFULL : BAR_BFULL0) + i * 8, (q ? q ^ t ^ 1 : t) & 1);
      const uint64_t adesc = adesc_q + ((i >> 1) * (A_SLOT >> 4) + (i & 1) * 4);
      const uint64_t bdesc = bdesc_q + i * (B_SLOT >> 4);
      wg_fence();
      wgmma_n256(acc, adesc, bdesc);
      wgmma_n256(acc, adesc + 2, bdesc + 128);
      wg_commit();
      if (i == NB - 1) { adesc_q += zero; bdesc_q += zero; }
    };
    auto retire = [&](int i, bool with_a) {
      wg_wait<2>();
      release((i + 6) & 7, with_a);
    };
    auto k_loop = [&](auto first, int t) __attribute__((always_inline)) {
      constexpr bool FIRST = decltype(first)::value;
      const bool inject = FIRST && brief && !helper;
      const uint32_t up = moves_up(t) ? B_SLOT >> 4 : 0;
      auto extras = [&](int q, int i, bool swap_now) __attribute__((always_inline)) {
        if (!FIRST) return;
        if (swap_now) swap_half(((i + 5) >> 1) & 3, (i + 1) & 1);
        if (!(i & 1) && q == capture_q) capture_slot(i >> 1);
      };
      auto free_partial = [&](int c) {
        if (FIRST) mbar_arrive_if(sb + BAR_PFREE + chunk_of(c) * 8, inject && rel_b);
      };
      extras(0, 0, false);
#pragma unroll
      for (int i = 1; i < 8; i++) {
        if (!(i & 1)) PROF(t * 32 + wg * 16 + 8 + (i >> 1));
        if ((i == 1 || i == 7) && inject) add_partial(i >> 2);
        issue(i, 0, t, true);
        if (i >= 2) retire(i, rel_ab);
        if (i == 3) free_partial(0);
        extras(0, i, i >= 3 && swap);
      }
      PROF(t * 32 + wg * 16 + 1);
      if (!FIRST || !brief) {
#pragma unroll 1
        for (int q = 1; q < 3; q++) {
#pragma unroll
          for (int i = 0; i < 8; i++) {
            issue(i, q | 4, t, true);
            if (i == 0) PROF(t * 32 + wg * 16 + 3 + q);
            retire(i, rel_ab);
            extras(q, i, i < 3 && swap);
          }
          if (FIRST) swap = false;
          if (q == 1) bdesc_q += up;
        }
      }
      const bool rel_last = rel_b | (hold & rel_ab);
      auto with_a = [&](int slot) { return slot == 7 ? rel_ab : rel_last; };
      uint32_t delay = 0;
      constexpr int JOIN = DRAIN + 2;
      constexpr int INJ = JOIN < 3 ? 3 : JOIN;
#pragma unroll
      for (int i = 0; i < DRAIN; i++) {
        issue(i, 3, t, true);
        retire(i, with_a((i + 6) & 7));
        if (i == 1) free_partial(1);
        extras(3, i, i < 3 && swap);
      }
      if (wg == 1) {
        wg_wait<1>();
        release((DRAIN + 6) & 7, with_a((DRAIN + 6) & 7));
        wg_wait<0>();
        release((DRAIN + 7) & 7, with_a((DRAIN + 7) & 7));
        if (DRAIN < 2) free_partial(1);
        PROF(t * 32 + wg * 16 + 12);
#pragma unroll
        for (int i = DRAIN; i < 3; i++) extras(-2, i, swap);
        mbar_spin(sb + BAR_ORDER, t & 1);
        PROF(t * 32 + wg * 16 + 6);
#pragma unroll
        for (int i = DRAIN; i < JOIN; i++) {
          issue(i, 3, t, true);
          extras(3, i, false);
        }
      } else {
        PROF(t * 32 + wg * 16 + 6);
#pragma unroll
        for (int i = DRAIN; i < JOIN; i++) {
          issue(i, 3, t, true);
          retire(i, with_a((i + 6) & 7));
          if (i == 1) free_partial(1);
          extras(3, i, i < 3 && swap);
        }
      }
#pragma unroll
      for (int i = JOIN; i < 8; i++) {
        if ((i == INJ || i == 7) && inject) add_partial(i == INJ ? 2 : 3);
        if (!FIRST && i == 3) asm volatile("ld.relaxed.cta.shared.u32 %0, [%1];" : "=r"(delay) : "r"(sb + OFF_DELAY + wg * 4) : "memory");
        if (!FIRST && i == 5) {
          asm volatile("{\n.reg .pred p;\n.reg .u32 a, b;\nsetp.eq.u32 p, %0, 0;\n@p bra.uni DONE;\nmov.u32 a, %%clock;\n"
                       "WAIT:\nmov.u32 b, %%clock;\nsub.u32 b, b, a;\nsetp.lt.u32 p, b, %0;\n@p bra.uni WAIT;\nDONE:\n}" ::"r"(delay) : "memory");
        }
        issue(i, 3, t, true);
        if (i == 7) mbar_arrive_if(sb + BAR_ORDER, rel_b & (wg == 0));
        retire(i, rel_last);
        if (i == INJ + 2) free_partial(2);
        extras(3, i, false);
      }
      bdesc_q -= up;
    };

    auto epilogue = [&](auto kind, int t, bool more) __attribute__((always_inline)) {
      constexpr int KIND = decltype(kind)::value;
      constexpr int PRE = KIND == 0 ? BPRE : (KIND == 1 ? HPRE : 0);
      if (KIND != 1 && t == 0) mbar_spin(sb + BAR_BIAS, 0);
      const uint32_t bl = sb + OFF_BIAS + (KIND == 1 ? kLayers - 1 : l) * 512 + ((frag0 >> 3) & 0x30);
      uint32_t bq[8][4];
      auto load_bias = [&](int U) {
        asm volatile("ld.shared.v4.u32 {%0, %1, %2, %3}, [%4];"
                     : "=r"(bq[U][0]), "=r"(bq[U][1]), "=r"(bq[U][2]), "=r"(bq[U][3]) : "r"(bl + U * 64));
      };
#pragma unroll
      for (int U = 0; U < PRE; U++) load_bias(U);
      wg_wait<1>();
      release(6, false);
      if (more) mbar_spin(sb + BAR_BFULL0, (t + 1) & 1);
      wg_wait<0>();
#pragma unroll
      for (int i = 0; i < 128; i++) asm volatile("" : "+f"(acc[i]) :: "memory");
      release(7, KIND == 0 ? rel_b : (KIND == 1 ? rel_ab : rel_b | (more & rel_ab)));
      PROF(t * 32 + wg * 16 + 2);
      if (t == 0) PROF_ST(30 + wg);

      auto pack = [&](int i, float off) {
        uint32_t v;
        asm("cvt.rn.bf16x2.f32 %0, %1, %2;" : "=r"(v) : "f"(acc[i * 2 + 1] - off), "f"(acc[i * 2] - off));
        return v;
      };
      auto cross = [&](int T, int i, float off) {
        uint32_t s2 = pack(T * 4 + i, off), o;
        asm("add.rn.bf16x2 %0, %1, %2;" : "=r"(s2) : "r"(s2), "r"(bq[T >> 1][(T & 1) * 2 + (i >> 1)]));
        asm("fma.rn.bf16x2 %0, %1, %2, %1;" : "=r"(o) : "r"(xr[T * 4 + i]), "r"(s2));
        return o;
      };
      auto reset = [&](int T) {
#pragma unroll
        for (int i = T * 8; i < T * 8 + 8; i += 4)
          asm volatile("ld.volatile.shared.v4.f32 {%0, %1, %2, %3}, [%4];"
                       : "+f"(acc[i]), "+f"(acc[i + 1]), "+f"(acc[i + 2]), "+f"(acc[i + 3]) : "r"(sb + OFF_INIT));
      };
      auto offset_for = [&](int T) { return T >= LAG ? acc[(T - LAG) * 8 + 7] : kOffset; };
      if (KIND == 2) {
        uint32_t id;
        asm volatile("mov.u32 %0, %%tid.x;" : "=r"(id));
        __nv_bfloat16* dst = optr + (size_t)(job_row(t) + wg * 64) * kDim + j * 256 + (id & 127) * 2;
        uint64_t pol;
        asm volatile("createpolicy.fractional.L2::evict_first.b64 %0, 1.0;" : "=l"(pol));
#pragma unroll
        for (int T = 0; T < 16; T++) {
#pragma unroll
          for (int i = 0; i < 4; i++)
            asm volatile("st.global.L2::cache_hint.b32 [%0], %1, %2;"
                         ::"l"(dst + (T * 4 + (i ^ 1)) * kDim), "r"(pack(T * 4 + i, offset_for(T))), "l"(pol) : "memory");
          reset(T);
        }
        asm volatile("bar.sync %0, 128;" ::"r"(wg + 1) : "memory");
        mbar_arrive_if(sb + BAR_PUB + wg * 8, rel_b);
      } else if (KIND == 1) {
#pragma unroll
        for (int T = 0; T < 16; T++) {
#pragma unroll
          for (int i = 0; i < 4; i++) xr[T * 4 + i] = cross(T, i, offset_for(T));
          if ((T & 1) && (T >> 1) + PRE < 8) load_bias((T >> 1) + PRE);
          reset(T);
        }
      } else {
#pragma unroll
        for (int T = 0; T < 16; T++) {
          uint32_t o[4];
#pragma unroll
          for (int i = 0; i < 4; i++) o[i] = cross(T, i, kOffset);
          stsm4((frag0 ^ ((T & 3) * 32)) + (T >> 2) * A_SLOT, o);
          if ((T & 3) == 3) chunk_staged(T >> 2);
          if ((T & 1) && (T >> 1) + PRE < 8) load_bias((T >> 1) + PRE);
        }
        PROF(t * 32 + wg * 16 + 7);
      }
      PROF(t * 32 + wg * 16 + 3);
    };

    PROF_ST(8);
    cluster_wait();
    PROF_ST(9);
    mbar_spin(sb + BAR_BFULL0, 0);
    PROF_ST(10);
    int t = 0;
#pragma unroll 1
    while (true) {
      if (t > 0) {
        if (helper) {
          epilogue(Int<2>(), t - 1, t < kJobs);
          if (t == kJobs) break;
        } else {
          epilogue(Int<1>(), t - 1, true);
        }
      }
      issue(0, 0, 0, false);
      if (t == 0) PROF_ST(11);
      l = 0;
      swap = t > 0 && !helper;
      brief = helper || t == short_t;
      hold = helper && t + 1 < kJobs;
      capture_q = (t > 0 || helper) ? -1 : j;
      PROF(t * 32 + wg * 16 + 0);
      k_loop(Flag<true>(), t);
      t++;
      if (helper) continue;
#pragma unroll 1
      do {
        epilogue(Int<0>(), t - 1, t < kTiles);
        if (t == kTiles) asm volatile("exit;");
        issue(0, 0, 0, false);
        l++;
        hold = l == kLayers - 1 && t + 1 < kTiles;
        PROF(t * 32 + wg * 16 + 0);
        k_loop(Flag<false>(), t);
        t++;
      } while (!hold);
    }
  }
}

__global__ void __launch_bounds__(256) dcn_fallback(const __nv_bfloat16* __restrict__ x0, const __nv_bfloat16* __restrict__ w,
                                                    const __nv_bfloat16* __restrict__ b, __nv_bfloat16* __restrict__ out) {
  __shared__ float xs[8][kDim];
  const size_t r0 = (size_t)blockIdx.x * 8;
  for (int i = threadIdx.x; i < 8 * kDim; i += 256) xs[i / kDim][i % kDim] = __bfloat162float(x0[r0 * kDim + i]);
  __syncthreads();
  for (int l = 0; l < kLayers; l++) {
    float a[4][8] = {};
    for (int k = 0; k < kDim; k++) {
#pragma unroll
      for (int c = 0; c < 4; c++) {
        const float wv = __bfloat162float(w[((size_t)l * kDim + k) * kDim + c * 256 + threadIdx.x]);
#pragma unroll
        for (int r = 0; r < 8; r++) a[c][r] += xs[r][k] * wv;
      }
    }
    __syncthreads();
#pragma unroll
    for (int c = 0; c < 4; c++) {
      const int n = c * 256 + threadIdx.x;
#pragma unroll
      for (int r = 0; r < 8; r++) {
        const float v = __bfloat162float(x0[(r0 + r) * kDim + n]) * (a[c][r] + __bfloat162float(b[l * kDim + n])) + xs[r][n];
        xs[r][n] = __bfloat162float(__float2bfloat16(v));
      }
    }
    __syncthreads();
  }
  for (int i = threadIdx.x; i < 8 * kDim; i += 256) out[r0 * kDim + i] = __float2bfloat16(xs[i / kDim][i % kDim]);
}

typedef CUresult (*EncodeFn)(CUtensorMap*, CUtensorMapDataType, cuuint32_t, void*, const cuuint64_t*, const cuuint64_t*,
                             const cuuint32_t*, const cuuint32_t*, CUtensorMapInterleave, CUtensorMapSwizzle,
                             CUtensorMapL2promotion, CUtensorMapFloatOOBfill);

static void make_map_2d(EncodeFn enc, CUtensorMap* m, void* ptr, uint64_t rows, uint32_t box_rows,
                        CUtensorMapSwizzle swizzle = CU_TENSOR_MAP_SWIZZLE_128B) {
  cuuint64_t dims[2] = {(cuuint64_t)kDim, rows};
  cuuint64_t strides[1] = {kDim * 2};
  cuuint32_t box[2] = {64, box_rows};
  cuuint32_t es[2] = {1, 1};
  enc(m, CU_TENSOR_MAP_DATA_TYPE_BFLOAT16, 2, ptr, dims, strides, box, es, CU_TENSOR_MAP_INTERLEAVE_NONE,
      swizzle, CU_TENSOR_MAP_L2_PROMOTION_L2_128B, CU_TENSOR_MAP_FLOAT_OOB_FILL_NONE);
}

}

extern "C" void kernel_launch(void* const* d_in, const int* in_sizes, int n_in, void* d_out, int out_size) {
  using namespace dcn;
  (void)in_sizes; (void)n_in; (void)out_size;
  void* fn = nullptr;
  cudaDriverEntryPointQueryResult qr;
  cudaGetDriverEntryPoint("cuTensorMapEncodeTiled", &fn, cudaEnableDefault, &qr);
  EncodeFn enc = (EncodeFn)fn;
  CUtensorMap mx64, mx32, mo64, mo32, mw, mp;
  make_map_2d(enc, &mx64, d_in[0], kRows, 64);
  make_map_2d(enc, &mx32, d_in[0], kRows, 32);
  make_map_2d(enc, &mo64, d_out, kRows, 64);
  make_map_2d(enc, &mo32, d_out, kRows, 32);
  make_map_2d(enc, &mp, d_out, kRows, 64, CU_TENSOR_MAP_SWIZZLE_NONE);
  {
    cuuint64_t dims[3] = {64, (cuuint64_t)kLayers * kDim, kDim / 64};
    cuuint64_t strides[2] = {kDim * 2, 128};
    cuuint32_t box[3] = {64, 32, 4};
    cuuint32_t es[3] = {1, 1, 1};
    enc(&mw, CU_TENSOR_MAP_DATA_TYPE_BFLOAT16, 3, d_in[1], dims, strides, box, es, CU_TENSOR_MAP_INTERLEAVE_NONE,
        CU_TENSOR_MAP_SWIZZLE_128B, CU_TENSOR_MAP_L2_PROMOTION_L2_128B, CU_TENSOR_MAP_FLOAT_OOB_FILL_NONE);
  }
  const __nv_bfloat16* x0 = (const __nv_bfloat16*)d_in[0];
  const __nv_bfloat16* w = (const __nv_bfloat16*)d_in[1];
  const __nv_bfloat16* b = (const __nv_bfloat16*)d_in[2];
  __nv_bfloat16* out = (__nv_bfloat16*)d_out;
  constexpr int smem = SMEM_BYTES + PROF_SMEM;
  cudaFuncSetAttribute(dcn_kernel, cudaFuncAttributeMaxDynamicSharedMemorySize, smem);

  cudaLaunchConfig_t cfg = {};
  cfg.gridDim = dim3(4 * kGroups + 4);
  cfg.blockDim = dim3(384);
  cfg.dynamicSmemBytes = smem;
  cudaLaunchAttribute attr;
  attr.id = cudaLaunchAttributeClusterDimension;
  attr.val.clusterDim.x = 2;
  attr.val.clusterDim.y = 1;
  attr.val.clusterDim.z = 1;
  cfg.attrs = &attr;
  cfg.numAttrs = 1;
  int clusters = 0;
  cudaOccupancyMaxActiveClusters(&clusters, dcn_kernel, &cfg);
  if (clusters >= 2 * kGroups) {
    const int grid = 4 * kGroups + (clusters >= 2 * kGroups + 2 ? 4 : 0);
    dcn_kernel<<<grid, 384, smem>>>(x0, w, b, out, mx64, mx32, mo64, mo32, mw, mp);
  } else {
    dcn_fallback<<<kRows / 8, 256>>>(x0, w, b, out);
  }
}
```

```cpp
#include <cuda_runtime.h>
#include <cuda.h>
#include <cuda_bf16.h>
#include <stdint.h>

namespace dcn {

__device__ __forceinline__ void wgmma_n256(float (&d)[128], uint64_t da, uint64_t db) {
  asm volatile("wgmma.mma_async.sync.aligned.m64n256k16.f32.bf16.bf16 "
    "{%0, %1, %2, %3, %4, %5, %6, %7, %8, %9, %10, %11, %12, %13, %14, %15, %16, %17, %18, %19, %20, %21, %22, %23, %24, %25, %26, %27, %28, %29, %30, %31, %32, %33, %34, %35, %36, %37, %38, %39, %40, %41, %42, %43, %44, %45, %46, %47, %48, %49, %50, %51, %52, %53, %54, %55, %56, %57, %58, %59, %60, %61, %62, %63, %64, %65, %66, %67, %68, %69, %70, %71, %72, %73, %74, %75, %76, %77, %78, %79, %80, %81, %82, %83, %84, %85, %86, %87, %88, %89, %90, %91, %92, %93, %94, %95, %96, %97, %98, %99, %100, %101, %102, %103, %104, %105, %106, %107, %108, %109, %110, %111, %112, %113, %114, %115, %116, %117, %118, %119, %120, %121, %122, %123, %124, %125, %126, %127}, "
    "%128, %129, 1, 1, 1, 0, 1;\n"
    : "+f"(d[0]), "+f"(d[1]), "+f"(d[2]), "+f"(d[3]), "+f"(d[4]), "+f"(d[5]), "+f"(d[6]), "+f"(d[7]), "+f"(d[8]), "+f"(d[9]), "+f"(d[10]), "+f"(d[11]), "+f"(d[12]), "+f"(d[13]), "+f"(d[14]), "+f"(d[15]), "+f"(d[16]), "+f"(d[17]), "+f"(d[18]), "+f"(d[19]), "+f"(d[20]), "+f"(d[21]), "+f"(d[22]), "+f"(d[23]), "+f"(d[24]), "+f"(d[25]), "+f"(d[26]), "+f"(d[27]), "+f"(d[28]), "+f"(d[29]), "+f"(d[30]), "+f"(d[31]), "+f"(d[32]), "+f"(d[33]), "+f"(d[34]), "+f"(d[35]), "+f"(d[36]), "+f"(d[37]), "+f"(d[38]), "+f"(d[39]), "+f"(d[40]), "+f"(d[41]), "+f"(d[42]), "+f"(d[43]), "+f"(d[44]), "+f"(d[45]), "+f"(d[46]), "+f"(d[47]), "+f"(d[48]), "+f"(d[49]), "+f"(d[50]), "+f"(d[51]), "+f"(d[52]), "+f"(d[53]), "+f"(d[54]), "+f"(d[55]), "+f"(d[56]), "+f"(d[57]), "+f"(d[58]), "+f"(d[59]), "+f"(d[60]), "+f"(d[61]), "+f"(d[62]), "+f"(d[63]), "+f"(d[64]), "+f"(d[65]), "+f"(d[66]), "+f"(d[67]), "+f"(d[68]), "+f"(d[69]), "+f"(d[70]), "+f"(d[71]), "+f"(d[72]), "+f"(d[73]), "+f"(d[74]), "+f"(d[75]), "+f"(d[76]), "+f"(d[77]), "+f"(d[78]), "+f"(d[79]), "+f"(d[80]), "+f"(d[81]), "+f"(d[82]), "+f"(d[83]), "+f"(d[84]), "+f"(d[85]), "+f"(d[86]), "+f"(d[87]), "+f"(d[88]), "+f"(d[89]), "+f"(d[90]), "+f"(d[91]), "+f"(d[92]), "+f"(d[93]), "+f"(d[94]), "+f"(d[95]), "+f"(d[96]), "+f"(d[97]), "+f"(d[98]), "+f"(d[99]), "+f"(d[100]), "+f"(d[101]), "+f"(d[102]), "+f"(d[103]), "+f"(d[104]), "+f"(d[105]), "+f"(d[106]), "+f"(d[107]), "+f"(d[108]), "+f"(d[109]), "+f"(d[110]), "+f"(d[111]), "+f"(d[112]), "+f"(d[113]), "+f"(d[114]), "+f"(d[115]), "+f"(d[116]), "+f"(d[117]), "+f"(d[118]), "+f"(d[119]), "+f"(d[120]), "+f"(d[121]), "+f"(d[122]), "+f"(d[123]), "+f"(d[124]), "+f"(d[125]), "+f"(d[126]), "+f"(d[127])
    : "l"(da), "l"(db));
}

constexpr int kDim = 1024;
constexpr int kRows = 16384;
constexpr int kLayers = 6;
constexpr int kGroups = 32;
constexpr int kRounds = kRows / 128 / kGroups;
constexpr int kTiles = kRounds * kLayers;

constexpr int kJobs = kGroups;
constexpr int kEpoch = 32;
constexpr int NA = 4;
constexpr int NB = 8;
constexpr float kOffset = 85.333336f;
constexpr float kTrunc = 64 * 0.375f / 131072;
constexpr int DRAIN = 1;
constexpr int LAG = 3;
constexpr int BPRE = 5;
constexpr int HPRE = 6;
constexpr uint32_t kAlign = 0x412a;
constexpr int NF = 2;
constexpr int A_SLOT = 8192;
constexpr int B_SLOT = 16384;
constexpr int OFF_B = 0;
constexpr int NP = 3;
constexpr int OFF_P = OFF_B + NB * B_SLOT;
constexpr int OFF_A = OFF_P + NP * A_SLOT;
constexpr int OFF_UNIT = OFF_A + 2 * NA * A_SLOT;
constexpr int OFF_BIAS = OFF_UNIT + 2048;
constexpr int OFF_INIT = OFF_BIAS + kLayers * 256 * 2;
constexpr int OFF_DELAY = OFF_INIT + 16;
constexpr int OFF_BAR = OFF_DELAY + 16;
constexpr int BAR_BFULL = OFF_BAR;
constexpr int BAR_BFULL0 = BAR_BFULL + NB * 8;
constexpr int BAR_BEMPTY = BAR_BFULL0 + NB * 8;
constexpr int BAR_AFULL = BAR_BEMPTY + NB * 8;
constexpr int BAR_AEMPTY = BAR_AFULL + 2 * NA * 8;
constexpr int BAR_XREADY = BAR_AEMPTY + 2 * NA * 8;
constexpr int BAR_PUB = BAR_XREADY + 16;
constexpr int BAR_PFULL = BAR_PUB + 16;
constexpr int BAR_PFREE = BAR_PFULL + 8 * 8;
constexpr int BAR_STAGED = BAR_PFREE + 8 * 8;
constexpr int BAR_ORDER = BAR_STAGED + 2 * NA * 8;
constexpr int BAR_BIAS = BAR_ORDER + 8;
constexpr int SMEM_BYTES = BAR_BIAS + 8;
static_assert(SMEM_BYTES <= 232448, "shared memory budget");

constexpr int kFlagSet = 4 * (kGroups + 1) * 32;
__device__ unsigned int g_flags[3 * kFlagSet];
__device__ uint32_t g_phase[16 * 32];

__device__ __forceinline__ uint32_t smem_u32(const void* p) { return (uint32_t)__cvta_generic_to_shared(p); }
__device__ __forceinline__ void mbar_init(uint32_t bar, int cnt) {
  asm volatile("mbarrier.init.shared::cta.b64 [%0], %1;" ::"r"(bar), "r"(cnt) : "memory");
}
__device__ __forceinline__ void mbar_arrive(uint32_t bar) {
  asm volatile("mbarrier.arrive.shared::cta.b64 _, [%0];" ::"r"(bar) : "memory");
}
__device__ __forceinline__ uint32_t map_cta(uint32_t addr, uint32_t cta) {
  uint32_t r;
  asm volatile("mapa.shared::cluster.u32 %0, %1, %2;" : "=r"(r) : "r"(addr), "r"(cta));
  return r;
}
__device__ __forceinline__ void mbar_arrive_mapped_if(uint32_t cluster_addr, bool pred) {
  asm volatile("{\n.reg .pred p;\nsetp.ne.u32 p, %1, 0;\n@p mbarrier.arrive.shared::cluster.b64 _, [%0];\n}"
               ::"r"(cluster_addr), "r"((uint32_t)pred) : "memory");
}
__device__ __forceinline__ void mbar_arrive_if(uint32_t bar, bool pred) {
  asm volatile("{\n.reg .pred p;\nsetp.ne.u32 p, %1, 0;\n@p mbarrier.arrive.shared::cta.b64 _, [%0];\n}"
               ::"r"(bar), "r"((uint32_t)pred) : "memory");
}
__device__ __forceinline__ void mbar_wait(uint32_t bar, uint32_t parity) {
  asm volatile(
      "{\n.reg .pred p;\n.reg .u32 c;\n"
      "mbarrier.try_wait.parity.shared::cta.b64 p, [%0], %1;\n"
      "@p bra DONE;\n"
      "mov.u32 c, 0;\n"
      "LOOP:\n"
      "mbarrier.try_wait.parity.shared::cta.b64 p, [%0], %1;\n"
      "@p bra DONE;\n"
      "add.u32 c, c, 1;\n"
      "setp.lt.u32 p, c, 1048576;\n"
      "@p bra LOOP;\n"
      "trap;\n"
      "DONE:\n}"
      ::"r"(bar), "r"(parity) : "memory");
}
__device__ __forceinline__ bool mbar_watch(uint32_t bar, uint32_t parity, uint32_t later, uint32_t later_parity) {
  uint32_t seen;
  asm volatile(
      "{\n.reg .pred p;\n.reg .u32 c;\n"
      "mov.u32 %0, 0;\n"
      "mbarrier.test_wait.parity.shared::cta.b64 p, [%1], %2;\n"
      "@p bra DONE;\n"
      "mov.u32 c, 0;\n"
      "LOOP:\n"
      "mbarrier.try_wait.parity.shared::cta.b64 p, [%1], %2;\n"
      "selp.u32 %0, 1, 0, p;\n"
      "@p bra DONE;\n"
      "mbarrier.test_wait.parity.shared::cta.b64 p, [%3], %4;\n"
      "add.u32 c, c, 1;\n"
      "setp.ge.or.u32 p, c, 1048576, p;\n"
      "@!p bra LOOP;\n"
      "DONE:\n}"
      : "=r"(seen) : "r"(bar), "r"(parity), "r"(later), "r"(later_parity) : "memory");
  return __shfl_sync(0xffffffffu, seen, 0);
}
__device__ __forceinline__ void mbar_spin(uint32_t bar, uint32_t parity) {
  asm volatile(
      "{\n.reg .pred p;\n"
      "LOOP:\n"
      "mbarrier.try_wait.parity.shared::cta.b64 p, [%0], %1;\n"
      "@!p bra LOOP;\n}"
      ::"r"(bar), "r"(parity) : "memory");
}
#define ELECT_BEGIN "{\n.reg .pred e;\nelect.sync _|e, 0xffffffff;\n"
template <bool STREAM> __device__ __forceinline__ void expect_load_2d_e(uint32_t dst, const CUtensorMap* m, uint32_t bar, int c0, int c1) {
  if (STREAM) {
    asm volatile(ELECT_BEGIN ".reg .b64 pol;\ncreatepolicy.fractional.L2::evict_first.b64 pol, 1.0;\n"
                 "@e mbarrier.arrive.expect_tx.shared::cta.b64 _, [%2], 8192;\n"
                 "@e cp.async.bulk.tensor.2d.shared::cluster.global.mbarrier::complete_tx::bytes.L2::cache_hint [%0], [%1, {%3, %4}], [%2], pol;\n}"
                 ::"r"(dst), "l"(m), "r"(bar), "r"(c0), "r"(c1) : "memory");
  } else {
    asm volatile(ELECT_BEGIN
                 "@e mbarrier.arrive.expect_tx.shared::cta.b64 _, [%2], 8192;\n"
                 "@e cp.async.bulk.tensor.2d.shared::cluster.global.mbarrier::complete_tx::bytes [%0], [%1, {%3, %4}], [%2];\n}"
                 ::"r"(dst), "l"(m), "r"(bar), "r"(c0), "r"(c1) : "memory");
  }
}
__device__ __forceinline__ void expect_load_2d_mc_e(uint32_t dst, const CUtensorMap* m, uint32_t bar, int c0, int c1) {
  asm volatile(ELECT_BEGIN ".reg .b64 pol;\ncreatepolicy.fractional.L2::evict_first.b64 pol, 1.0;\n"
               "@e mbarrier.arrive.expect_tx.shared::cta.b64 _, [%2], 8192;\n"
               "@e cp.async.bulk.tensor.2d.shared::cluster.global.mbarrier::complete_tx::bytes.multicast::cluster.L2::cache_hint [%0], [%1, {%3, %4}], [%2], %5, pol;\n}"
               ::"r"(dst), "l"(m), "r"(bar), "r"(c0), "r"(c1), "h"((uint16_t)3) : "memory");
}
__device__ __forceinline__ void expect_load_3d_e(uint32_t dst, const CUtensorMap* m, uint32_t bar, int c0, int c1, int c2) {
  asm volatile(ELECT_BEGIN
               "@e mbarrier.arrive.expect_tx.shared::cta.b64 _, [%2], 16384;\n"
               "@e cp.async.bulk.tensor.3d.shared::cluster.global.mbarrier::complete_tx::bytes [%0], [%1, {%3, %4, %5}], [%2];\n}"
               ::"r"(dst), "l"(m), "r"(bar), "r"(c0), "r"(c1), "r"(c2) : "memory");
}
template <bool STREAM> __device__ __forceinline__ void store_2d_e(const CUtensorMap* m, uint32_t src, int c0, int c1) {
  if (STREAM) {
    asm volatile(ELECT_BEGIN ".reg .b64 pol;\ncreatepolicy.fractional.L2::evict_first.b64 pol, 1.0;\n"
                 "@e cp.async.bulk.tensor.2d.global.shared::cta.bulk_group.L2::cache_hint [%0, {%2, %3}], [%1], pol;\n}"
                 ::"l"(m), "r"(src), "r"(c0), "r"(c1) : "memory");
  } else {
    asm volatile(ELECT_BEGIN
                 "@e cp.async.bulk.tensor.2d.global.shared::cta.bulk_group [%0, {%2, %3}], [%1];\n}"
                 ::"l"(m), "r"(src), "r"(c0), "r"(c1) : "memory");
  }
}
__device__ __forceinline__ void prefetch_2d_e(const CUtensorMap* m, int c0, int c1) {
  asm volatile(ELECT_BEGIN
               "@e cp.async.bulk.prefetch.tensor.2d.L2.global [%0, {%1, %2}];\n}"
               ::"l"(m), "r"(c0), "r"(c1) : "memory");
}
__device__ __forceinline__ void prefetch_1d_e(const void* ptr, uint32_t bytes) {
  asm volatile(ELECT_BEGIN
               "@e cp.async.bulk.prefetch.L2.global [%0], %1;\n}"
               ::"l"(ptr), "r"(bytes) : "memory");
}
__device__ __forceinline__ void paced_load_3d_e(uint32_t dst, const CUtensorMap* m, uint32_t bar, int c0, int c1, int c2, bool pace) {
  asm volatile(ELECT_BEGIN ".reg .pred p;\nsetp.ne.u32 p, %6, 0;\n"
               "@e mbarrier.arrive.expect_tx.shared::cta.b64 _, [%2], 16384;\n"
               "@p nanosleep.u32 128;\n"
               "@e cp.async.bulk.tensor.3d.shared::cluster.global.mbarrier::complete_tx::bytes [%0], [%1, {%3, %4, %5}], [%2];\n}"
               ::"r"(dst), "l"(m), "r"(bar), "r"(c0), "r"(c1), "r"(c2), "r"((uint32_t)pace) : "memory");
}
__device__ __forceinline__ void arrive_mapped_e(uint32_t cluster_addr) {
  asm volatile(ELECT_BEGIN "@e mbarrier.arrive.shared::cluster.b64 _, [%0];\n}" ::"r"(cluster_addr) : "memory");
}
__device__ __forceinline__ void arrive_e(uint32_t bar) {
  asm volatile(ELECT_BEGIN "@e mbarrier.arrive.shared::cta.b64 _, [%0];\n}" ::"r"(bar) : "memory");
}
__device__ __forceinline__ void bulk_commit() { asm volatile("cp.async.bulk.commit_group;" ::: "memory"); }
template <int N> __device__ __forceinline__ void bulk_wait() { asm volatile("cp.async.bulk.wait_group %0;" ::"n"(N) : "memory"); }
__device__ __forceinline__ void wg_fence() { asm volatile("wgmma.fence.sync.aligned;" ::: "memory"); }
__device__ __forceinline__ void wg_commit() { asm volatile("wgmma.commit_group.sync.aligned;" ::: "memory"); }
template <int N> __device__ __forceinline__ void wg_wait() { asm volatile("wgmma.wait_group.sync.aligned %0;" ::"n"(N) : "memory"); }
__device__ __forceinline__ void fence_async_global() { asm volatile("fence.proxy.async.global;" ::: "memory"); }
__device__ __forceinline__ void st_relaxed(unsigned int* p, unsigned int v) {
  asm volatile("st.relaxed.gpu.global.u32 [%0], %1;" ::"l"(p), "r"(v) : "memory");
}
__device__ __forceinline__ void ldsm4(uint32_t* r, uint32_t addr) {
  asm volatile("ldmatrix.sync.aligned.m8n8.x4.shared.b16 {%0, %1, %2, %3}, [%4];"
               : "=r"(r[0]), "=r"(r[1]), "=r"(r[2]), "=r"(r[3]) : "r"(addr) : "memory");
}
__device__ __forceinline__ void stsm4(uint32_t addr, const uint32_t* r) {
  asm volatile("stmatrix.sync.aligned.m8n8.x4.shared.b16 [%0], {%1, %2, %3, %4};"
               ::"r"(addr), "r"(r[0]), "r"(r[1]), "r"(r[2]), "r"(r[3]) : "memory");
}
template <bool V> struct Flag { static constexpr bool value = V; };
template <int V> struct Int { static constexpr int value = V; };
__device__ __forceinline__ void fence_async_smem() { asm volatile("fence.proxy.async.shared::cta;" ::: "memory"); }
__device__ __forceinline__ void cluster_arrive_relaxed() { asm volatile("barrier.cluster.arrive.relaxed.aligned;" ::: "memory"); }
__device__ __forceinline__ void cluster_wait() { asm volatile("barrier.cluster.wait.acquire.aligned;" ::: "memory"); }
__device__ __forceinline__ void prefetch_map(const CUtensorMap* m) {
  asm volatile("prefetch.tensormap [%0];" ::"l"(m) : "memory");
}
__device__ __forceinline__ void prefetch_map_e(const CUtensorMap* m) {
  asm volatile(ELECT_BEGIN "@e prefetch.tensormap [%0];\n}" ::"l"(m) : "memory");
}
__device__ __forceinline__ void poll_flag(const unsigned int* ptr, unsigned int target) {
  asm volatile(
      "{\n.reg .pred p;\n.reg .u32 c;\n.reg .s32 v;\n"
      "mov.u32 c, 0;\n"
      "LOOP:\n"
      "ld.acquire.gpu.global.s32 v, [%0];\n"
      "sub.s32 v, v, %1;\n"
      "setp.ge.s32 p, v, 0;\n"
      "@p bra DONE;\n"
      "add.u32 c, c, 1;\n"
      "setp.lt.u32 p, c, 1048576;\n"
      "@p bra LOOP;\n"
      "trap;\n"
      "DONE:\n}"
      ::"l"(ptr), "r"(target) : "memory");
}

constexpr uint32_t DESC_HI = (1024u >> 4) | (1u << 30);
__device__ __forceinline__ uint64_t desc(uint32_t lo) { return ((uint64_t)DESC_HI << 32) | lo; }
constexpr uint32_t DESC_A_LBO = 1u << 16;
constexpr uint32_t DESC_B_LBO = (4096u >> 4) << 16;

__device__ __forceinline__ int kgroup_col(int j, int q) {
  return q == 0 ? j : (q == 1 ? (j ^ 1) : (((j ^ 2) & ~1) + (q - 2)));
}

__device__ __forceinline__ int role_of_cluster(int c) {
  const int a = c - 4;
  const int b = c - 36, r = (b * 37) >> 8;
  const int first = (a & ~7) + (a & 3) * 2 + ((a >> 2) & 1);
  const int second = 32 + r * 8 + ((0x7531640 >> (((b - r * 7) * 4) & 31)) & 7);
  return c >= 2 * kGroups ? c : (c >= 36 ? second : (c >= 4 ? first : 34 + c * 8));
}
__device__ __forceinline__ int helped_round(int grp) { return (grp & 2) ? (grp & 3) - 1 : 3; }
__device__ __forceinline__ int job_of_group(int grp) {
  return (grp & 2) ? (grp & 1) * 8 + (grp >> 2) : 16 + (grp >> 2) * 2 + (grp & 1);
}
__device__ __forceinline__ int job_row(int n) {
  const int grp = n < 16 ? (n & 7) * 4 + 2 + (n >> 3) : ((n - 16) >> 1) * 4 + (n & 1);
  return (helped_round(grp) * kGroups + grp) * 128;
}

constexpr int PROF_SMEM = 0;
#define PROF_BOTH(idx) do {} while (0)
#define PROF_SVC(idx) do {} while (0)
#define PROF_DUMP() do {} while (0)
#define PROF(idx) do {} while (0)
#define PROF_ST(idx) do {} while (0)
#define PROF_SKEW(idx) do {} while (0)

__global__ void __cluster_dims__(2, 1, 1) __launch_bounds__(384, 1)
dcn_kernel(const __nv_bfloat16* __restrict__ xptr, const __nv_bfloat16* __restrict__ wptr,
           const __nv_bfloat16* __restrict__ bias, __nv_bfloat16* optr,
           const __grid_constant__ CUtensorMap mx64, const __grid_constant__ CUtensorMap mx32,
           const __grid_constant__ CUtensorMap mo64, const __grid_constant__ CUtensorMap mo32,
           const __grid_constant__ CUtensorMap mw, const __grid_constant__ CUtensorMap mp) {
  extern __shared__ __align__(1024) uint8_t smem_raw[];
  const uint32_t sb = smem_u32(smem_raw);
  const int tid = threadIdx.x;
  if ((tid >> 5) == 8) PROF_ST(0);
  if ((tid >> 5) == 9) PROF_BOTH(48);
  const int wid = __shfl_sync(0xffffffffu, tid >> 5, 0);
  if (wid == 0) {
    asm volatile("prefetch.global.L2 [%0];" ::"l"(wptr + ((blockIdx.x & 31) * 32 + tid) * 64));
    asm volatile("prefetch.global.L2 [%0];" ::"l"(xptr + ((blockIdx.x & 127) * 32 + tid) * kDim));
    prefetch_map_e(&mw);
    prefetch_map_e(&mx64);
    PROF_ST(29);
  }
  const int bid = role_of_cluster(blockIdx.x >> 1) * 2 + (blockIdx.x & 1);
  const int j = bid & 3;
  const int grp = bid >> 2;
  const bool helper = grp == kGroups;
  const int col0 = helper ? kgroup_col(j, 2) * 256 : 0;
  const int row0 = helper ? job_row(0) : grp * 128;
  auto first_loads = [&](int s) {
    const int col = col0 + s * 64;
    expect_load_3d_e(sb + OFF_B + 2 * s * B_SLOT, &mw, sb + BAR_BFULL0 + 2 * s * 8, 0, col, j * 4);
    expect_load_2d_e<false>(sb + OFF_A + s * A_SLOT, &mx64, sb + BAR_AFULL + s * 8, col, row0);
    expect_load_3d_e(sb + OFF_B + (2 * s + 1) * B_SLOT, &mw, sb + BAR_BFULL0 + (2 * s + 1) * 8, 0, col + 32, j * 4);
    expect_load_2d_e<false>(sb + OFF_A + (NA + s) * A_SLOT, &mx64, sb + BAR_AFULL + (NA + s) * 8, col, row0 + 64);
    PROF_ST(2 + s);
  };
  auto init_full = [&](int s) {
    mbar_init(sb + BAR_BFULL0 + 2 * s * 8, 1);
    mbar_init(sb + BAR_BFULL0 + (2 * s + 1) * 8, 1);
    mbar_init(sb + BAR_AFULL + s * 8, 1);
    mbar_init(sb + BAR_AFULL + (NA + s) * 8, 1);
  };
  if (wid == 8) {
    PROF_ST(28);
    if (tid == 256) {
      init_full(0);
      asm volatile("fence.mbarrier_init.release.cluster;" ::: "memory");
    }
    __syncwarp();
    PROF_ST(1);
    first_loads(0);
    if (tid == 256) {
#pragma unroll
      for (int s = 1; s < 4; s++) init_full(s);
      asm volatile("fence.mbarrier_init.release.cluster;" ::: "memory");
    }
    __syncwarp();
#pragma unroll
    for (int s = 1; s < NF; s++) first_loads(s);
  }
  const int wg = wid >> 2;
  const int warp = wid & 3;
  const uint32_t rank = j & 1;
  const int short_t = (gridDim.x > 4 * kGroups && !helper) ? helped_round(grp) * kLayers : -8;
  const unsigned lend = helper ? ~0u : 1u;
  auto moves_up = [&](int t) { return (unsigned)(t + 1 - short_t) > lend; };

  if (wg == 2) {
    asm volatile("setmaxnreg.dec.sync.aligned.u32 40;");
    if (tid == 288) {
      if (sb & 1023) asm volatile("trap;");
#pragma unroll
      for (int i = 0; i < NB; i++) { mbar_init(sb + BAR_BFULL + i * 8, 1); mbar_init(sb + BAR_BEMPTY + i * 8, 2); }
#pragma unroll
      for (int i = 0; i < 4; i++) mbar_init(sb + BAR_XREADY + i * 8, 1);
      mbar_init(sb + BAR_ORDER, 1);
    } else if (tid == 320) {
#pragma unroll
      for (int i = 0; i < 2 * NA; i++) { mbar_init(sb + BAR_AEMPTY + i * 8, 2); mbar_init(sb + BAR_STAGED + i * 8, 4); }
    } else if (tid == 352) {
#pragma unroll
      for (int i = 0; i < 8; i++) { mbar_init(sb + BAR_PFULL + i * 8, 1); mbar_init(sb + BAR_PFREE + i * 8, 1); }
      mbar_init(sb + BAR_BIAS, 32);
      asm volatile("st.shared.v4.f32 [%0], {%1, %1, %1, %1};" ::"r"(sb + OFF_INIT), "f"(kOffset) : "memory");
      asm volatile("st.shared.v2.u32 [%0], {0, 0};" ::"r"(sb + OFF_DELAY) : "memory");
    }
    asm volatile("fence.mbarrier_init.release.cluster;" ::: "memory");
    __syncwarp();
    cluster_arrive_relaxed();
    if (warp == 0) {
      PROF_ST(6);
#pragma unroll 1
      for (int s = NF; s < 4; s++) first_loads(s);
      cluster_wait();
      PROF_ST(7);
      uint32_t par = 0;
      int l = 0;
      const int ntiles = helper ? kJobs : kTiles;
#pragma unroll 1
      for (int t = 0; t < ntiles; t++) {
        const int jo = (t == 0 && !helper) ? 0 : j;
        const int q_end = t == short_t ? 2 : 4;
#pragma unroll 1
        for (int q = (helper ? 2 : 0) + (t == 0); q < q_end; q++) {
          const int krow = l * kDim + kgroup_col(jo, q) * 256;
          const bool first = q == (helper ? 2 : 0);
          const bool up = q >= 2 && moves_up(t);
          const int shift = first ? (moves_up(t - 1) ? -1 : 0) : (up && q == 2 ? 1 : 0);
          const int paced = first ? (shift ? DRAIN + 1 : 0) : ((helper || (q == 1 && (t == short_t || t == 0))) ? 0 : NB);
          const uint32_t dst = sb + OFF_B + (up ? B_SLOT : 0);
          const uint32_t full = sb + (first ? BAR_BFULL0 : BAR_BFULL);
          if (shift > 0) mbar_spin(sb + BAR_BEMPTY, par);
#pragma unroll 1
          for (int i = 0; i < NB; i++) {
            if ((unsigned)(i + shift) < NB) mbar_spin(sb + BAR_BEMPTY + (i + shift) * 8, par);
            paced_load_3d_e(dst + i * B_SLOT, &mw, full + i * 8, 0, krow + i * 32, j * 4, i < paced);
            PROF_SKEW(t * 32 + q * 8 + i);
          }
          if (shift < 0) mbar_spin(sb + BAR_BEMPTY + (NB - 1) * 8, par);
          par ^= 1;
        }
        if (helper || ++l == kLayers) l = 0;
      }
    } else if (warp <= 2) {
      const int w = warp - 1;
      const uint32_t abase = sb + OFF_A + w * NA * A_SLOT;
      const uint32_t fullb = sb + BAR_AFULL + w * NA * 8;
      const uint32_t emptyb = sb + BAR_AEMPTY + w * 8;
      const uint32_t stagedb = sb + BAR_STAGED + w * NA * 8;
      const unsigned int base = __shfl_sync(0xffffffffu, *(volatile unsigned int*)(g_flags + bid * 32), 0);
      cluster_wait();
      uint32_t epar = 0;
      uint32_t spar = 0;
      auto refill = [&](const CUtensorMap* m, int col, int row) {
#pragma unroll 1
        for (int s = 0; s < 4; s++) {
          mbar_spin(emptyb + s * 16, epar);
          expect_load_2d_e<false>(abase + s * A_SLOT, m, fullb + s * 8, col + s * 64, row);
        }
        epar ^= 1;
      };
      auto store_refill = [&](int out_row, int col, int row, bool last_read) {
#pragma unroll 1
        for (int s = 0; s < 4; s++) {
          mbar_spin(stagedb + s * 8, spar);
          fence_async_smem();
          store_2d_e<true>(&mo64, abase + s * A_SLOT, j * 256 + s * 64, out_row);
          bulk_commit();
          bulk_wait<0>();
          __syncwarp();
          mbar_spin(emptyb + s * 16, epar);
          if (last_read) expect_load_2d_e<true>(abase + s * A_SLOT, &mx64, fullb + s * 8, col + s * 64, row);
          else expect_load_2d_e<false>(abase + s * A_SLOT, &mx64, fullb + s * 8, col + s * 64, row);
        }
        spar ^= 1;
        epar ^= 1;
      };
      auto store_tile = [&](auto stream, int out_row) {
#pragma unroll 1
        for (int c = 0; c < 4; c++) {
          mbar_spin(stagedb + c * 8, spar);
          fence_async_smem();
          arrive_e(fullb + c * 8);
          if (!decltype(stream)::value && w == 1) {
            bulk_commit();
            bulk_wait<0>();
          }
          store_2d_e<decltype(stream)::value>(&mo64, abase + c * A_SLOT, j * 256 + c * 64, out_row);
        }
        spar ^= 1;
        bulk_commit();
        bulk_wait<0>();
        __syncwarp();
      };
      auto refill_shared = [&](const CUtensorMap* m32, int col, int row) {
#pragma unroll 1
        for (int s = 0; s < 4; s++) {
          mbar_spin(emptyb + s * 16, epar);
          expect_load_2d_mc_e(abase + s * A_SLOT + rank * 4096, m32, fullb + s * 8, col + s * 64, row + rank * 32);
        }
        epar ^= 1;
      };
      if (helper) {
#pragma unroll 1
        for (int h = 1; h < 2 * kJobs; h++) refill_shared(&mx32, col0 + (h & 1) * 256, job_row(h >> 1) + w * 64);
      } else {
        const uint32_t xready_peer = map_cta(sb + BAR_XREADY + w * 8, rank ^ 1);
        const unsigned int* oflag = g_flags + (grp * 4 + kgroup_col(j, 2)) * 32;
        unsigned int* done_mine = g_flags + kFlagSet + (bid * 2 + w) * 32;
        const unsigned int* done_peer = g_flags + kFlagSet + ((bid ^ 2) * 2 + w) * 32;
        uint32_t nx = 0;
#pragma unroll 1
        for (int rd = 0; rd < kRounds; rd++) {
          const int xrow = (rd * kGroups + grp) * 128 + w * 64;
          if (rd == 0) {
            refill(&mx64, 256, xrow);
          } else {
            poll_flag(done_peer, base + nx);
            store_refill(xrow - kGroups * 128, (j ^ 1) * 256, xrow, rd * kLayers == short_t);
          }
          if (rd * kLayers != short_t) {
#pragma unroll 1
            for (int h = 0; h < 2; h++) refill_shared(&mx32, (kgroup_col(rd == 0 ? 0 : j, 2) + h) * 256, xrow);
          }
#pragma unroll 1
          for (int l = 1; l < kLayers; l++) {
            if (l > 1) poll_flag(done_peer, base + nx);
            store_tile(Flag<false>(), xrow);
            PROF_SVC((rd * kLayers + l - 1) * 2 + w);
            arrive_mapped_e(xready_peer);
            arrive_e(sb + BAR_PUB + w * 8);
            mbar_spin(sb + BAR_XREADY + w * 8, nx & 1);
            fence_async_global();
            refill(&mo64, (j ^ 1) * 256, xrow);
#pragma unroll 1
            for (int h = 0; h < 2; h++) {
              poll_flag(oflag + h * 32, base + nx + 1);
              fence_async_global();
              refill_shared(&mo32, (kgroup_col(j, 2) + h) * 256, xrow);
            }
            if (rank) {
#pragma unroll 1
              for (int s = 0; s < 4; s++) mbar_spin(fullb + s * 8, 1);
            }
            nx++;
            if ((tid & 31) == 0) st_relaxed(done_mine, base + (nx == kRounds * (kLayers - 1) ? kEpoch : nx));
            __syncwarp();
          }
          const int nrow = xrow + kGroups * 128;
          if (rd + 1 == kRounds) {
            poll_flag(done_peer, base + nx);
            store_tile(Flag<true>(), xrow);
            PROF_SVC((rd * kLayers + kLayers - 1) * 2 + w);
            arrive_e(sb + BAR_PUB + w * 8);
          } else {
            refill(&mx64, j * 256, nrow);
            PROF_SVC((rd * kLayers + kLayers - 1) * 2 + w);
          }
        }
      }
    } else {
      const int lane = tid & 31;
      unsigned int* myflag = g_flags + bid * 32;
      if (lane == 0) { prefetch_map(&mx32); prefetch_map(&mo64); prefetch_map(&mo32); }
      const unsigned int base = *(volatile unsigned int*)myflag;
      auto publish = [&](uint32_t n, uint32_t value) {
#pragma unroll 1
        for (int w = 0; w < 2; w++) mbar_wait(sb + BAR_PUB + w * 8, n & 1);
        if (lane == 0) asm volatile("st.release.gpu.global.u32 [%0], %1;" ::"l"(myflag), "r"(base + value) : "memory");
        __syncwarp();
      };
      if (helper) {
        mbar_arrive(sb + BAR_BIAS);
        cluster_wait();
#pragma unroll 1
        for (int n = 0; n < kJobs; n++) {
          if (n + 2 < kJobs) {
            const int row = job_row(n + 2);
#pragma unroll 1
            for (int i = 0; i < 8; i++) prefetch_2d_e(&mx64, col0 + rank * 256 + (i & 3) * 64, row + (i >> 2) * 64);
          }
          publish(n, n + 1);
        }
      } else {
        {
          float c[8];
#pragma unroll
          for (int i = 0; i < 8; i++) c[i] = 0.f;
#pragma unroll 1
          for (int l = 0; l < kLayers; l++) {
            const uint4 v = *reinterpret_cast<const uint4*>(bias + l * kDim + j * 256 + lane * 8);
            const uint32_t u[4] = {v.x, v.y, v.z, v.w};
#pragma unroll
            for (int i = 0; i < 4; i++) {
              c[2 * i] += __uint_as_float(u[i] << 16) + kTrunc;
              c[2 * i + 1] += __uint_as_float(u[i] & 0xffff0000u) + kTrunc;
              uint32_t pk;
              asm("cvt.rn.bf16x2.f32 %0, %1, %2;" : "=r"(pk) : "f"(c[2 * i + 1]), "f"(c[2 * i]));
              asm volatile("st.shared.u32 [%0], %1;" ::"r"(sb + OFF_BIAS + l * 512 + (lane >> 2) * 64 + i * 16 + (lane & 3) * 4),
                           "r"(pk) : "memory");
            }
          }
#pragma unroll
          for (int i = 0; i < 15; i++) {
            const uint32_t one = (lane >> 3) == (lane & 3) ? 0x3f80u << ((lane & 4) * 4) : 0u;
            asm volatile("st.shared.u32 [%0], %1;" ::"r"(sb + OFF_UNIT + i * 128 + lane * 4), "r"(i == 7 ? one : 0u) : "memory");
          }
          fence_async_smem();
          mbar_arrive(sb + BAR_BIAS);
        }
        const __nv_bfloat16* wslice = wptr + bid * 8192;
        cluster_wait();
        prefetch_1d_e(wslice + kDim * kDim, 16384);
        uint32_t nx = 0;
#pragma unroll 1
        for (int rd = 0; rd < kRounds; rd++) {
#pragma unroll 1
          for (int l = 1; l < kLayers; l++) {
            const int t = rd * kLayers + l;
            const bool align = ((kAlign >> t) & 1) &&
                               mbar_watch(sb + BAR_STAGED + NA * 8, (t - 1) & 1, sb + BAR_PUB + 8, nx & 1);
            uint32_t mine = 0, tick = 0;
            if (align) {
              uint32_t c0, c1;
              asm volatile("mov.u32 %0, %%clock;\nnanosleep.u32 128;\nmov.u32 %1, %%clock;\nmov.u32 %2, %%globaltimer_lo;\n"
                           "nanosleep.u32 128;\nmov.u32 %3, %%clock;"
                           : "=r"(c0), "=r"(c1), "=r"(mine), "=r"(tick) :: "memory");
              tick -= c1;
              mine = ((mine + 64) >> 8 << 10) - (c1 - c0);
            }
            publish(nx, nx + 1 == kRounds * (kLayers - 1) ? kEpoch : nx + 1);
            nx++;
            {
              uint32_t delay = 0;
              if (align) {
                unsigned int* line = g_phase + (bid & 15) * 32;
                if (lane == 0) st_relaxed(line + (grp >> 2), mine);
                __syncwarp();
#pragma unroll 1
                for (int i = 0; i < 3; i++) __nanosleep(256);
                uint32_t other;
                asm volatile("ld.relaxed.gpu.global.u32 %0, [%1];" : "=r"(other) : "l"(line + (lane & 7)) : "memory");
                const int ticks = (int)(((other + 1023) & ~1023u) - ((mine + 1023) & ~1023u)) >> 10;
                const int lag = ticks * (int)tick - (int)((-other & 1023) - (-mine & 1023));
                const int far = __reduce_max_sync(0xffffffffu, ((unsigned)ticks < 4 && lag < 700) ? lag : 0);
                delay = far > 40 ? far + 280 : 0;
              }
              asm volatile("st.relaxed.cta.shared.u32 [%0], %1;" ::"r"(sb + OFF_DELAY), "r"(delay) : "memory");
            }
            if (l < kLayers - 1 && rd == 0) prefetch_1d_e(wslice + (l + 1) * kDim * kDim, 16384);
            if (l > 1 && rd + 1 < kRounds) {
              const int nrow = ((rd + 1) * kGroups + grp) * 128;
              prefetch_1d_e(xptr + (size_t)(nrow + j * 32 + l * 8 - 16) * kDim, 8192);
              __nanosleep(600);
              prefetch_1d_e(xptr + (size_t)(nrow + j * 32 + l * 8 - 12) * kDim, 8192);
              if (rd * kLayers + l + 1 == short_t) {
                poll_flag(g_flags + (4 * kGroups + j) * 32, base + job_of_group(grp) + 1);
                fence_async_global();
                constexpr uint32_t order = 0x76325140;
#pragma unroll 1
                for (int i = NP; i < 8; i++)
                  prefetch_2d_e(&mp, j * 256 + ((order >> (i * 4)) & 3) * 64, nrow + ((order >> (i * 4)) & 4) * 16);
#pragma unroll 1
                for (int i = 0; i < 8; i++) {
                  if (i >= NP) mbar_wait(sb + BAR_PFREE + (i - NP) * 8, 0);
                  PROF(776 + i);
                  expect_load_2d_e<true>(sb + OFF_P + (i % NP) * A_SLOT, &mp, sb + BAR_PFULL + i * 8,
                                         j * 256 + ((order >> (i * 4)) & 3) * 64, nrow + ((order >> (i * 4)) & 4) * 16);
                }
              }
            }
          }
        }
#pragma unroll 1
        for (int w = 0; w < 2; w++) mbar_wait(sb + BAR_PUB + w * 8, nx & 1);
      }
    }
    if (warp == 3) PROF_DUMP();
  } else {
    cluster_arrive_relaxed();
    asm volatile("setmaxnreg.inc.sync.aligned.u32 232;");
    PROF_ST(32);
    const int lane = tid & 31;
    const int wtid = tid & 127;
    const uint32_t abase = sb + OFF_A + wg * NA * A_SLOT;
    const uint32_t afull = sb + BAR_AFULL + wg * NA * 8;
    const uint32_t rel = map_cta(sb + (wtid == 64 ? BAR_BEMPTY : BAR_AEMPTY + wg * 8 - 8), wtid == 32 ? (rank ^ 1) : rank);
    const bool rel_b = wtid == 64;
    const bool rel_ab = (wtid & 31) == 0 && wtid < 96;
    const uint32_t frag0 = __shfl_sync(0xffffffffu, abase + ((wtid >> 5) * 16 + ((lane >> 3) & 1) * 8 + (lane & 7)) * 128 +
                                                        (((lane >> 4) ^ (lane & 7)) << 4), lane);
    const uint64_t adesc0 = desc(((abase & 0x3FFFF) >> 4) | DESC_A_LBO);
    const uint64_t bdesc0 = desc((((sb + OFF_B) & 0x3FFFF) >> 4) | DESC_B_LBO);

    const uint64_t zero = gridDim.y - 1;
    uint64_t adesc_q = adesc0 + zero, bdesc_q = bdesc0 + zero;

    float acc[128];
    uint32_t xr[64];
#pragma unroll
    for (int i = 0; i < 128; i++) acc[i] = kOffset;
#pragma unroll
    for (int i = 0; i < 64; i++) xr[i] = 0;
    int l = 0;
    bool hold = false;
    bool swap = false;
    bool brief = helper;
    int capture_q = helper ? -1 : j;

    auto release = [&](int i, bool with_a) {
      mbar_arrive_mapped_if(rel + i * 8, (i & 1) ? with_a : rel_b);
    };
    auto chunk_staged = [&](int c) {
      __syncwarp();
      arrive_e(sb + BAR_STAGED + (wg * NA + c) * 8);
    };
    auto capture_slot = [&](int p) {
#pragma unroll
      for (int g = 0; g < 4; g++) ldsm4(&xr[(p * 4 + g) * 4], (frag0 ^ (g * 32)) + p * A_SLOT);
    };
    auto swap_half = [&](int p, int half) {
#pragma unroll
      for (int g = half * 2; g < half * 2 + 2; g++) {
        const uint32_t addr = (frag0 ^ (g * 32)) + p * A_SLOT;
        uint32_t n[4];
        ldsm4(n, addr);
        stsm4(addr, &xr[(p * 4 + g) * 4]);
#pragma unroll
        for (int i = 0; i < 4; i++) xr[(p * 4 + g) * 4 + i] = n[i];
      }
      if (half) chunk_staged(p);
    };
    auto chunk_of = [&](int c) { return wg ? (0x7631 >> (c * 4)) & 7 : (0x5420 >> (c * 4)) & 7; };
    auto add_partial = [&](int c) __attribute__((always_inline)) {
      const int n = chunk_of(c);
      const int slot = wg ? (0x1001 >> (c * 4)) & 3 : (0x2120 >> (c * 4)) & 3;
      PROF(768 + wg * 16 + c * 2);
      mbar_spin(sb + BAR_PFULL + n * 8, 0);
      PROF(768 + wg * 16 + c * 2 + 1);
      wg_fence();
      wgmma_n256(acc, ((uint64_t)(128 >> 4) << 32) | ((128 >> 4) << 16) | (((sb + OFF_UNIT + (6 - 2 * c) * 128) & 0x3FFFF) >> 4),
                 ((uint64_t)(256 >> 4) << 32) | ((128 >> 4) << 16) | (((sb + OFF_P + slot * A_SLOT) & 0x3FFFF) >> 4));
    };
    auto issue = [&](int i, int q, int t, bool wait_b) __attribute__((always_inline)) {
      if (!(i & 1)) mbar_spin(afull + (i >> 1) * 8, q & 1);
      if (wait_b) mbar_spin(sb + (q ? BAR_BFULL : BAR_BFULL0) + i * 8, (q ? q ^ t ^ 1 : t) & 1);
      const uint64_t adesc = adesc_q + ((i >> 1) * (A_SLOT >> 4) + (i & 1) * 4);
      const uint64_t bdesc = bdesc_q + i * (B_SLOT >> 4);
      wg_fence();
      wgmma_n256(acc, adesc, bdesc);
      wgmma_n256(acc, adesc + 2, bdesc + 128);
      wg_commit();
      if (i == NB - 1) { adesc_q += zero; bdesc_q += zero; }
    };
    auto retire = [&](int i, bool with_a) {
      wg_wait<2>();
      release((i + 6) & 7, with_a);
    };
    auto k_loop = [&](auto first, int t) __attribute__((always_inline)) {
      constexpr bool FIRST = decltype(first)::value;
      const bool inject = FIRST && brief && !helper;
      const uint32_t up = moves_up(t) ? B_SLOT >> 4 : 0;
      auto extras = [&](int q, int i, bool swap_now) __attribute__((always_inline)) {
        if (!FIRST) return;
        if (swap_now) swap_half(((i + 5) >> 1) & 3, (i + 1) & 1);
        if (!(i & 1) && q == capture_q) capture_slot(i >> 1);
      };
      auto free_partial = [&](int c) {
        if (FIRST) mbar_arrive_if(sb + BAR_PFREE + chunk_of(c) * 8, inject && rel_b);
      };
      extras(0, 0, false);
#pragma unroll
      for (int i = 1; i < 8; i++) {
        if (!(i & 1)) PROF(t * 32 + wg * 16 + 8 + (i >> 1));
        if ((i == 1 || i == 7) && inject) add_partial(i >> 2);
        issue(i, 0, t, true);
        if (i >= 2) retire(i, rel_ab);
        if (i == 3) free_partial(0);
        extras(0, i, i >= 3 && swap);
      }
      PROF(t * 32 + wg * 16 + 1);
      if (!FIRST || !brief) {
#pragma unroll 1
        for (int q = 1; q < 3; q++) {
#pragma unroll
          for (int i = 0; i < 8; i++) {
            issue(i, q | 4, t, true);
            if (i == 0) PROF(t * 32 + wg * 16 + 3 + q);
            retire(i, rel_ab);
            extras(q, i, i < 3 && swap);
          }
          if (FIRST) swap = false;
          if (q == 1) bdesc_q += up;
        }
      }
      const bool rel_last = rel_b | (hold & rel_ab);
      auto with_a = [&](int slot) { return slot == 7 ? rel_ab : rel_last; };
      uint32_t delay = 0;
      constexpr int JOIN = DRAIN + 2;
      constexpr int INJ = JOIN < 3 ? 3 : JOIN;
#pragma unroll
      for (int i = 0; i < DRAIN; i++) {
        issue(i, 3, t, true);
        retire(i, with_a((i + 6) & 7));
        if (i == 1) free_partial(1);
        extras(3, i, i < 3 && swap);
      }
      if (wg == 1) {
        wg_wait<1>();
        release((DRAIN + 6) & 7, with_a((DRAIN + 6) & 7));
        wg_wait<0>();
        release((DRAIN + 7) & 7, with_a((DRAIN + 7) & 7));
        if (DRAIN < 2) free_partial(1);
        PROF(t * 32 + wg * 16 + 12);
#pragma unroll
        for (int i = DRAIN; i < 3; i++) extras(-2, i, swap);
        mbar_spin(sb + BAR_ORDER, t & 1);
        PROF(t * 32 + wg * 16 + 6);
#pragma unroll
        for (int i = DRAIN; i < JOIN; i++) {
          issue(i, 3, t, true);
          extras(3, i, false);
        }
      } else {
        PROF(t * 32 + wg * 16 + 6);
#pragma unroll
        for (int i = DRAIN; i < JOIN; i++) {
          issue(i, 3, t, true);
          retire(i, with_a((i + 6) & 7));
          if (i == 1) free_partial(1);
          extras(3, i, i < 3 && swap);
        }
      }
#pragma unroll
      for (int i = JOIN; i < 8; i++) {
        if ((i == INJ || i == 7) && inject) add_partial(i == INJ ? 2 : 3);
        if (!FIRST && i == 3) asm volatile("ld.relaxed.cta.shared.u32 %0, [%1];" : "=r"(delay) : "r"(sb + OFF_DELAY + wg * 4) : "memory");
        if (!FIRST && i == 5) {
          asm volatile("{\n.reg .pred p;\n.reg .u32 a, b;\nsetp.eq.u32 p, %0, 0;\n@p bra.uni DONE;\nmov.u32 a, %%clock;\n"
                       "WAIT:\nmov.u32 b, %%clock;\nsub.u32 b, b, a;\nsetp.lt.u32 p, b, %0;\n@p bra.uni WAIT;\nDONE:\n}" ::"r"(delay) : "memory");
        }
        issue(i, 3, t, true);
        if (i == 7) mbar_arrive_if(sb + BAR_ORDER, rel_b & (wg == 0));
        retire(i, rel_last);
        if (i == INJ + 2) free_partial(2);
        extras(3, i, false);
      }
      bdesc_q -= up;
    };

    auto epilogue = [&](auto kind, int t, bool more) __attribute__((always_inline)) {
      constexpr int KIND = decltype(kind)::value;
      constexpr int PRE = KIND == 0 ? BPRE : (KIND == 1 ? HPRE : 0);
      if (KIND != 1 && t == 0) mbar_spin(sb + BAR_BIAS, 0);
      const uint32_t bl = sb + OFF_BIAS + (KIND == 1 ? kLayers - 1 : l) * 512 + ((frag0 >> 3) & 0x30);
      uint32_t bq[8][4];
      auto load_bias = [&](int U) {
        asm volatile("ld.shared.v4.u32 {%0, %1, %2, %3}, [%4];"
                     : "=r"(bq[U][0]), "=r"(bq[U][1]), "=r"(bq[U][2]), "=r"(bq[U][3]) : "r"(bl + U * 64));
      };
#pragma unroll
      for (int U = 0; U < PRE; U++) load_bias(U);
      wg_wait<1>();
      release(6, false);
      if (more) mbar_spin(sb + BAR_BFULL0, (t + 1) & 1);
      wg_wait<0>();
#pragma unroll
      for (int i = 0; i < 128; i++) asm volatile("" : "+f"(acc[i]) :: "memory");
      release(7, KIND == 0 ? rel_b : (KIND == 1 ? rel_ab : rel_b | (more & rel_ab)));
      PROF(t * 32 + wg * 16 + 2);
      if (t == 0) PROF_ST(30 + wg);

      auto pack = [&](int i, float off) {
        uint32_t v;
        asm("cvt.rn.bf16x2.f32 %0, %1, %2;" : "=r"(v) : "f"(acc[i * 2 + 1] - off), "f"(acc[i * 2] - off));
        return v;
      };
      auto cross = [&](int T, int i, float off) {
        uint32_t s2 = pack(T * 4 + i, off), o;
        asm("add.rn.bf16x2 %0, %1, %2;" : "=r"(s2) : "r"(s2), "r"(bq[T >> 1][(T & 1) * 2 + (i >> 1)]));
        asm("fma.rn.bf16x2 %0, %1, %2, %1;" : "=r"(o) : "r"(xr[T * 4 + i]), "r"(s2));
        return o;
      };
      auto reset = [&](int T) {
#pragma unroll
        for (int i = T * 8; i < T * 8 + 8; i += 4)
          asm volatile("ld.volatile.shared.v4.f32 {%0, %1, %2, %3}, [%4];"
                       : "+f"(acc[i]), "+f"(acc[i + 1]), "+f"(acc[i + 2]), "+f"(acc[i + 3]) : "r"(sb + OFF_INIT));
      };
      auto offset_for = [&](int T) { return T >= LAG ? acc[(T - LAG) * 8 + 7] : kOffset; };
      if (KIND == 2) {
        uint32_t id;
        asm volatile("mov.u32 %0, %%tid.x;" : "=r"(id));
        __nv_bfloat16* dst = optr + (size_t)(job_row(t) + wg * 64) * kDim + j * 256 + (id & 127) * 2;
        uint64_t pol;
        asm volatile("createpolicy.fractional.L2::evict_first.b64 %0, 1.0;" : "=l"(pol));
#pragma unroll
        for (int T = 0; T < 16; T++) {
#pragma unroll
          for (int i = 0; i < 4; i++)
            asm volatile("st.global.L2::cache_hint.b32 [%0], %1, %2;"
                         ::"l"(dst + (T * 4 + (i ^ 1)) * kDim), "r"(pack(T * 4 + i, offset_for(T))), "l"(pol) : "memory");
          reset(T);
        }
        asm volatile("bar.sync %0, 128;" ::"r"(wg + 1) : "memory");
        mbar_arrive_if(sb + BAR_PUB + wg * 8, rel_b);
      } else if (KIND == 1) {
#pragma unroll
        for (int T = 0; T < 16; T++) {
#pragma unroll
          for (int i = 0; i < 4; i++) xr[T * 4 + i] = cross(T, i, offset_for(T));
          if ((T & 1) && (T >> 1) + PRE < 8) load_bias((T >> 1) + PRE);
          reset(T);
        }
      } else {
#pragma unroll
        for (int T = 0; T < 16; T++) {
          uint32_t o[4];
#pragma unroll
          for (int i = 0; i < 4; i++) o[i] = cross(T, i, kOffset);
          stsm4((frag0 ^ ((T & 3) * 32)) + (T >> 2) * A_SLOT, o);
          if ((T & 3) == 3) chunk_staged(T >> 2);
          if ((T & 1) && (T >> 1) + PRE < 8) load_bias((T >> 1) + PRE);
        }
        PROF(t * 32 + wg * 16 + 7);
      }
      PROF(t * 32 + wg * 16 + 3);
    };

    PROF_ST(8);
    cluster_wait();
    PROF_ST(9);
    mbar_spin(sb + BAR_BFULL0, 0);
    PROF_ST(10);
    int t = 0;
#pragma unroll 1
    while (true) {
      if (t > 0) {
        if (helper) {
          epilogue(Int<2>(), t - 1, t < kJobs);
          if (t == kJobs) break;
        } else {
          epilogue(Int<1>(), t - 1, true);
        }
      }
      issue(0, 0, 0, false);
      if (t == 0) PROF_ST(11);
      l = 0;
      swap = t > 0 && !helper;
      brief = helper || t == short_t;
      hold = helper && t + 1 < kJobs;
      capture_q = (t > 0 || helper) ? -1 : j;
      PROF(t * 32 + wg * 16 + 0);
      k_loop(Flag<true>(), t);
      t++;
      if (helper) continue;
#pragma unroll 1
      do {
        epilogue(Int<0>(), t - 1, t < kTiles);
        if (t == kTiles) asm volatile("exit;");
        issue(0, 0, 0, false);
        l++;
        hold = l == kLayers - 1 && t + 1 < kTiles;
        PROF(t * 32 + wg * 16 + 0);
        k_loop(Flag<false>(), t);
        t++;
      } while (!hold);
    }
  }
}

__global__ void __launch_bounds__(256) dcn_fallback(const __nv_bfloat16* __restrict__ x0, const __nv_bfloat16* __restrict__ w,
                                                    const __nv_bfloat16* __restrict__ b, __nv_bfloat16* __restrict__ out) {
  __shared__ float xs[8][kDim];
  const size_t r0 = (size_t)blockIdx.x * 8;
  for (int i = threadIdx.x; i < 8 * kDim; i += 256) xs[i / kDim][i % kDim] = __bfloat162float(x0[r0 * kDim + i]);
  __syncthreads();
  for (int l = 0; l < kLayers; l++) {
    float a[4][8] = {};
    for (int k = 0; k < kDim; k++) {
#pragma unroll
      for (int c = 0; c < 4; c++) {
        const float wv = __bfloat162float(w[((size_t)l * kDim + k) * kDim + c * 256 + threadIdx.x]);
#pragma unroll
        for (int r = 0; r < 8; r++) a[c][r] += xs[r][k] * wv;
      }
    }
    __syncthreads();
#pragma unroll
    for (int c = 0; c < 4; c++) {
      const int n = c * 256 + threadIdx.x;
#pragma unroll
      for (int r = 0; r < 8; r++) {
        const float v = __bfloat162float(x0[(r0 + r) * kDim + n]) * (a[c][r] + __bfloat162float(b[l * kDim + n])) + xs[r][n];
        xs[r][n] = __bfloat162float(__float2bfloat16(v));
      }
    }
    __syncthreads();
  }
  for (int i = threadIdx.x; i < 8 * kDim; i += 256) out[r0 * kDim + i] = __float2bfloat16(xs[i / kDim][i % kDim]);
}

typedef CUresult (*EncodeFn)(CUtensorMap*, CUtensorMapDataType, cuuint32_t, void*, const cuuint64_t*, const cuuint64_t*,
                             const cuuint32_t*, const cuuint32_t*, CUtensorMapInterleave, CUtensorMapSwizzle,
                             CUtensorMapL2promotion, CUtensorMapFloatOOBfill);

static void make_map_2d(EncodeFn enc, CUtensorMap* m, void* ptr, uint64_t rows, uint32_t box_rows,
                        CUtensorMapSwizzle swizzle = CU_TENSOR_MAP_SWIZZLE_128B) {
  cuuint64_t dims[2] = {(cuuint64_t)kDim, rows};
  cuuint64_t strides[1] = {kDim * 2};
  cuuint32_t box[2] = {64, box_rows};
  cuuint32_t es[2] = {1, 1};
  enc(m, CU_TENSOR_MAP_DATA_TYPE_BFLOAT16, 2, ptr, dims, strides, box, es, CU_TENSOR_MAP_INTERLEAVE_NONE,
      swizzle, CU_TENSOR_MAP_L2_PROMOTION_L2_128B, CU_TENSOR_MAP_FLOAT_OOB_FILL_NONE);
}

}

extern "C" void kernel_launch(void* const* d_in, const int* in_sizes, int n_in, void* d_out, int out_size) {
  using namespace dcn;
  (void)in_sizes; (void)n_in; (void)out_size;
  void* fn = nullptr;
  cudaDriverEntryPointQueryResult qr;
  cudaGetDriverEntryPoint("cuTensorMapEncodeTiled", &fn, cudaEnableDefault, &qr);
  EncodeFn enc = (EncodeFn)fn;
  CUtensorMap mx64, mx32, mo64, mo32, mw, mp;
  make_map_2d(enc, &mx64, d_in[0], kRows, 64);
  make_map_2d(enc, &mx32, d_in[0], kRows, 32);
  make_map_2d(enc, &mo64, d_out, kRows, 64);
  make_map_2d(enc, &mo32, d_out, kRows, 32);
  make_map_2d(enc, &mp, d_out, kRows, 64, CU_TENSOR_MAP_SWIZZLE_NONE);
  {
    cuuint64_t dims[3] = {64, (cuuint64_t)kLayers * kDim, kDim / 64};
    cuuint64_t strides[2] = {kDim * 2, 128};
    cuuint32_t box[3] = {64, 32, 4};
    cuuint32_t es[3] = {1, 1, 1};
    enc(&mw, CU_TENSOR_MAP_DATA_TYPE_BFLOAT16, 3, d_in[1], dims, strides, box, es, CU_TENSOR_MAP_INTERLEAVE_NONE,
        CU_TENSOR_MAP_SWIZZLE_128B, CU_TENSOR_MAP_L2_PROMOTION_L2_128B, CU_TENSOR_MAP_FLOAT_OOB_FILL_NONE);
  }
  const __nv_bfloat16* x0 = (const __nv_bfloat16*)d_in[0];
  const __nv_bfloat16* w = (const __nv_bfloat16*)d_in[1];
  const __nv_bfloat16* b = (const __nv_bfloat16*)d_in[2];
  __nv_bfloat16* out = (__nv_bfloat16*)d_out;
  constexpr int smem = SMEM_BYTES + PROF_SMEM;
  cudaFuncSetAttribute(dcn_kernel, cudaFuncAttributeMaxDynamicSharedMemorySize, smem);

  cudaLaunchConfig_t cfg = {};
  cfg.gridDim = dim3(4 * kGroups + 4);
  cfg.blockDim = dim3(384);
  cfg.dynamicSmemBytes = smem;
  cudaLaunchAttribute attr;
  attr.id = cudaLaunchAttributeClusterDimension;
  attr.val.clusterDim.x = 2;
  attr.val.clusterDim.y = 1;
  attr.val.clusterDim.z = 1;
  cfg.attrs = &attr;
  cfg.numAttrs = 1;
  int clusters = 0;
  cudaOccupancyMaxActiveClusters(&clusters, dcn_kernel, &cfg);
  if (clusters >= 2 * kGroups) {
    const int grid = 4 * kGroups + (clusters >= 2 * kGroups + 2 ? 4 : 0);
    dcn_kernel<<<grid, 384, smem>>>(x0, w, b, out, mx64, mx32, mo64, mo32, mw, mp);
  } else {
    dcn_fallback<<<kRows / 8, 256>>>(x0, w, b, out);
  }
}
```

```cpp
#include <cuda_runtime.h>
#include <cuda.h>
#include <cuda_bf16.h>
#include <stdint.h>

namespace dcn {

__device__ __forceinline__ void wgmma_n256(float (&d)[128], uint64_t da, uint64_t db) {
  asm volatile("wgmma.mma_async.sync.aligned.m64n256k16.f32.bf16.bf16 "
    "{%0, %1, %2, %3, %4, %5, %6, %7, %8, %9, %10, %11, %12, %13, %14, %15, %16, %17, %18, %19, %20, %21, %22, %23, %24, %25, %26, %27, %28, %29, %30, %31, %32, %33, %34, %35, %36, %37, %38, %39, %40, %41, %42, %43, %44, %45, %46, %47, %48, %49, %50, %51, %52, %53, %54, %55, %56, %57, %58, %59, %60, %61, %62, %63, %64, %65, %66, %67, %68, %69, %70, %71, %72, %73, %74, %75, %76, %77, %78, %79, %80, %81, %82, %83, %84, %85, %86, %87, %88, %89, %90, %91, %92, %93, %94, %95, %96, %97, %98, %99, %100, %101, %102, %103, %104, %105, %106, %107, %108, %109, %110, %111, %112, %113, %114, %115, %116, %117, %118, %119, %120, %121, %122, %123, %124, %125, %126, %127}, "
    "%128, %129, 1, 1, 1, 0, 1;\n"
    : "+f"(d[0]), "+f"(d[1]), "+f"(d[2]), "+f"(d[3]), "+f"(d[4]), "+f"(d[5]), "+f"(d[6]), "+f"(d[7]), "+f"(d[8]), "+f"(d[9]), "+f"(d[10]), "+f"(d[11]), "+f"(d[12]), "+f"(d[13]), "+f"(d[14]), "+f"(d[15]), "+f"(d[16]), "+f"(d[17]), "+f"(d[18]), "+f"(d[19]), "+f"(d[20]), "+f"(d[21]), "+f"(d[22]), "+f"(d[23]), "+f"(d[24]), "+f"(d[25]), "+f"(d[26]), "+f"(d[27]), "+f"(d[28]), "+f"(d[29]), "+f"(d[30]), "+f"(d[31]), "+f"(d[32]), "+f"(d[33]), "+f"(d[34]), "+f"(d[35]), "+f"(d[36]), "+f"(d[37]), "+f"(d[38]), "+f"(d[39]), "+f"(d[40]), "+f"(d[41]), "+f"(d[42]), "+f"(d[43]), "+f"(d[44]), "+f"(d[45]), "+f"(d[46]), "+f"(d[47]), "+f"(d[48]), "+f"(d[49]), "+f"(d[50]), "+f"(d[51]), "+f"(d[52]), "+f"(d[53]), "+f"(d[54]), "+f"(d[55]), "+f"(d[56]), "+f"(d[57]), "+f"(d[58]), "+f"(d[59]), "+f"(d[60]), "+f"(d[61]), "+f"(d[62]), "+f"(d[63]), "+f"(d[64]), "+f"(d[65]), "+f"(d[66]), "+f"(d[67]), "+f"(d[68]), "+f"(d[69]), "+f"(d[70]), "+f"(d[71]), "+f"(d[72]), "+f"(d[73]), "+f"(d[74]), "+f"(d[75]), "+f"(d[76]), "+f"(d[77]), "+f"(d[78]), "+f"(d[79]), "+f"(d[80]), "+f"(d[81]), "+f"(d[82]), "+f"(d[83]), "+f"(d[84]), "+f"(d[85]), "+f"(d[86]), "+f"(d[87]), "+f"(d[88]), "+f"(d[89]), "+f"(d[90]), "+f"(d[91]), "+f"(d[92]), "+f"(d[93]), "+f"(d[94]), "+f"(d[95]), "+f"(d[96]), "+f"(d[97]), "+f"(d[98]), "+f"(d[99]), "+f"(d[100]), "+f"(d[101]), "+f"(d[102]), "+f"(d[103]), "+f"(d[104]), "+f"(d[105]), "+f"(d[106]), "+f"(d[107]), "+f"(d[108]), "+f"(d[109]), "+f"(d[110]), "+f"(d[111]), "+f"(d[112]), "+f"(d[113]), "+f"(d[114]), "+f"(d[115]), "+f"(d[116]), "+f"(d[117]), "+f"(d[118]), "+f"(d[119]), "+f"(d[120]), "+f"(d[121]), "+f"(d[122]), "+f"(d[123]), "+f"(d[124]), "+f"(d[125]), "+f"(d[126]), "+f"(d[127])
    : "l"(da), "l"(db));
}

constexpr int kDim = 1024;
constexpr int kRows = 16384;
constexpr int kLayers = 6;
constexpr int kGroups = 32;
constexpr int kRounds = kRows / 128 / kGroups;
constexpr int kTiles = kRounds * kLayers;

constexpr int kJobs = kGroups;
constexpr int kEpoch = 32;
constexpr int NA = 4;
constexpr int NB = 8;
constexpr float kOffset = 85.333336f;
constexpr float kTrunc = 64 * 0.375f / 131072;
constexpr int DRAIN = 1;
constexpr int LAG = 3;
constexpr int BPRE = 5;
constexpr int HPRE = 6;
constexpr uint32_t kAlign = 0x412a;
constexpr int A_SLOT = 8192;
constexpr int B_SLOT = 16384;
constexpr int OFF_B = 0;
constexpr int NP = 3;
constexpr int OFF_P = OFF_B + NB * B_SLOT;
constexpr int OFF_A = OFF_P + NP * A_SLOT;
constexpr int OFF_UNIT = OFF_A + 2 * NA * A_SLOT;
constexpr int OFF_BIAS = OFF_UNIT + 2048;
constexpr int OFF_INIT = OFF_BIAS + kLayers * 256 * 2;
constexpr int OFF_DELAY = OFF_INIT + 128;
constexpr int OFF_BAR = OFF_DELAY + 16;
constexpr int BAR_BFULL = OFF_BAR;
constexpr int BAR_BFULL0 = BAR_BFULL + NB * 8;
constexpr int BAR_BEMPTY = BAR_BFULL0 + NB * 8;
constexpr int BAR_AFULL = BAR_BEMPTY + NB * 8;
constexpr int BAR_AEMPTY = BAR_AFULL + 2 * NA * 8;
constexpr int BAR_XREADY = BAR_AEMPTY + 2 * NA * 8;
constexpr int BAR_PUB = BAR_XREADY + 16;
constexpr int BAR_PFULL = BAR_PUB + 16;
constexpr int BAR_PFREE = BAR_PFULL + 8 * 8;
constexpr int BAR_STAGED = BAR_PFREE + 8 * 8;
constexpr int BAR_ORDER = BAR_STAGED + 2 * NA * 8;
constexpr int BAR_BIAS = BAR_ORDER + 8;
constexpr int SMEM_BYTES = BAR_BIAS + 8;
static_assert(SMEM_BYTES <= 232448, "shared memory budget");

constexpr int kFlagSet = 4 * (kGroups + 1) * 32;
__device__ unsigned int g_flags[3 * kFlagSet];
__device__ uint32_t g_phase[16 * 32];

__device__ __forceinline__ uint32_t smem_u32(const void* p) { return (uint32_t)__cvta_generic_to_shared(p); }
__device__ __forceinline__ void mbar_init(uint32_t bar, int cnt) {
  asm volatile("mbarrier.init.shared::cta.b64 [%0], %1;" ::"r"(bar), "r"(cnt) : "memory");
}
__device__ __forceinline__ void mbar_arrive(uint32_t bar) {
  asm volatile("mbarrier.arrive.shared::cta.b64 _, [%0];" ::"r"(bar) : "memory");
}
__device__ __forceinline__ uint32_t map_cta(uint32_t addr, uint32_t cta) {
  uint32_t r;
  asm volatile("mapa.shared::cluster.u32 %0, %1, %2;" : "=r"(r) : "r"(addr), "r"(cta));
  return r;
}
__device__ __forceinline__ void mbar_arrive_mapped_if(uint32_t cluster_addr, bool pred) {
  asm volatile("{\n.reg .pred p;\nsetp.ne.u32 p, %1, 0;\n@p mbarrier.arrive.shared::cluster.b64 _, [%0];\n}"
               ::"r"(cluster_addr), "r"((uint32_t)pred) : "memory");
}
__device__ __forceinline__ void mbar_arrive_if(uint32_t bar, bool pred) {
  asm volatile("{\n.reg .pred p;\nsetp.ne.u32 p, %1, 0;\n@p mbarrier.arrive.shared::cta.b64 _, [%0];\n}"
               ::"r"(bar), "r"((uint32_t)pred) : "memory");
}
__device__ __forceinline__ void mbar_wait(uint32_t bar, uint32_t parity) {
  asm volatile(
      "{\n.reg .pred p;\n.reg .u32 c;\n"
      "mbarrier.try_wait.parity.shared::cta.b64 p, [%0], %1;\n"
      "@p bra DONE;\n"
      "mov.u32 c, 0;\n"
      "LOOP:\n"
      "mbarrier.try_wait.parity.shared::cta.b64 p, [%0], %1;\n"
      "@p bra DONE;\n"
      "add.u32 c, c, 1;\n"
      "setp.lt.u32 p, c, 1048576;\n"
      "@p bra LOOP;\n"
      "trap;\n"
      "DONE:\n}"
      ::"r"(bar), "r"(parity) : "memory");
}
__device__ __forceinline__ bool mbar_watch(uint32_t bar, uint32_t parity, uint32_t later, uint32_t later_parity) {
  uint32_t seen;
  asm volatile(
      "{\n.reg .pred p;\n.reg .u32 c;\n"
      "mov.u32 %0, 0;\n"
      "mbarrier.test_wait.parity.shared::cta.b64 p, [%1], %2;\n"
      "@p bra DONE;\n"
      "mov.u32 c, 0;\n"
      "LOOP:\n"
      "mbarrier.try_wait.parity.shared::cta.b64 p, [%1], %2;\n"
      "selp.u32 %0, 1, 0, p;\n"
      "@p bra DONE;\n"
      "mbarrier.test_wait.parity.shared::cta.b64 p, [%3], %4;\n"
      "add.u32 c, c, 1;\n"
      "setp.ge.or.u32 p, c, 1048576, p;\n"
      "@!p bra LOOP;\n"
      "DONE:\n}"
      : "=r"(seen) : "r"(bar), "r"(parity), "r"(later), "r"(later_parity) : "memory");
  return __shfl_sync(0xffffffffu, seen, 0);
}
__device__ __forceinline__ void mbar_spin(uint32_t bar, uint32_t parity) {
  asm volatile(
      "{\n.reg .pred p;\n"
      "LOOP:\n"
      "mbarrier.try_wait.parity.shared::cta.b64 p, [%0], %1;\n"
      "@!p bra LOOP;\n}"
      ::"r"(bar), "r"(parity) : "memory");
}
#define ELECT_BEGIN "{\n.reg .pred e;\nelect.sync _|e, 0xffffffff;\n"
template <bool STREAM> __device__ __forceinline__ void expect_load_2d_e(uint32_t dst, const CUtensorMap* m, uint32_t bar, int c0, int c1) {
  if (STREAM) {
    asm volatile(ELECT_BEGIN ".reg .b64 pol;\ncreatepolicy.fractional.L2::evict_first.b64 pol, 1.0;\n"
                 "@e mbarrier.arrive.expect_tx.shared::cta.b64 _, [%2], 8192;\n"
                 "@e cp.async.bulk.tensor.2d.shared::cluster.global.mbarrier::complete_tx::bytes.L2::cache_hint [%0], [%1, {%3, %4}], [%2], pol;\n}"
                 ::"r"(dst), "l"(m), "r"(bar), "r"(c0), "r"(c1) : "memory");
  } else {
    asm volatile(ELECT_BEGIN
                 "@e mbarrier.arrive.expect_tx.shared::cta.b64 _, [%2], 8192;\n"
                 "@e cp.async.bulk.tensor.2d.shared::cluster.global.mbarrier::complete_tx::bytes [%0], [%1, {%3, %4}], [%2];\n}"
                 ::"r"(dst), "l"(m), "r"(bar), "r"(c0), "r"(c1) : "memory");
  }
}
__device__ __forceinline__ void expect_load_2d_mc_e(uint32_t dst, const CUtensorMap* m, uint32_t bar, int c0, int c1) {
  asm volatile(ELECT_BEGIN ".reg .b64 pol;\ncreatepolicy.fractional.L2::evict_first.b64 pol, 1.0;\n"
               "@e mbarrier.arrive.expect_tx.shared::cta.b64 _, [%2], 8192;\n"
               "@e cp.async.bulk.tensor.2d.shared::cluster.global.mbarrier::complete_tx::bytes.multicast::cluster.L2::cache_hint [%0], [%1, {%3, %4}], [%2], %5, pol;\n}"
               ::"r"(dst), "l"(m), "r"(bar), "r"(c0), "r"(c1), "h"((uint16_t)3) : "memory");
}
__device__ __forceinline__ void expect_load_3d_e(uint32_t dst, const CUtensorMap* m, uint32_t bar, int c0, int c1, int c2) {
  asm volatile(ELECT_BEGIN
               "@e mbarrier.arrive.expect_tx.shared::cta.b64 _, [%2], 16384;\n"
               "@e cp.async.bulk.tensor.3d.shared::cluster.global.mbarrier::complete_tx::bytes [%0], [%1, {%3, %4, %5}], [%2];\n}"
               ::"r"(dst), "l"(m), "r"(bar), "r"(c0), "r"(c1), "r"(c2) : "memory");
}
template <bool STREAM> __device__ __forceinline__ void store_2d_e(const CUtensorMap* m, uint32_t src, int c0, int c1) {
  if (STREAM) {
    asm volatile(ELECT_BEGIN ".reg .b64 pol;\ncreatepolicy.fractional.L2::evict_first.b64 pol, 1.0;\n"
                 "@e cp.async.bulk.tensor.2d.global.shared::cta.bulk_group.L2::cache_hint [%0, {%2, %3}], [%1], pol;\n}"
                 ::"l"(m), "r"(src), "r"(c0), "r"(c1) : "memory");
  } else {
    asm volatile(ELECT_BEGIN
                 "@e cp.async.bulk.tensor.2d.global.shared::cta.bulk_group [%0, {%2, %3}], [%1];\n}"
                 ::"l"(m), "r"(src), "r"(c0), "r"(c1) : "memory");
  }
}
__device__ __forceinline__ void prefetch_2d_e(const CUtensorMap* m, int c0, int c1) {
  asm volatile(ELECT_BEGIN
               "@e cp.async.bulk.prefetch.tensor.2d.L2.global [%0, {%1, %2}];\n}"
               ::"l"(m), "r"(c0), "r"(c1) : "memory");
}
__device__ __forceinline__ void prefetch_1d_e(const void* ptr, uint32_t bytes) {
  asm volatile(ELECT_BEGIN
               "@e cp.async.bulk.prefetch.L2.global [%0], %1;\n}"
               ::"l"(ptr), "r"(bytes) : "memory");
}
__device__ __forceinline__ void paced_load_3d_e(uint32_t dst, const CUtensorMap* m, uint32_t bar, int c0, int c1, int c2, bool pace) {
  asm volatile(ELECT_BEGIN ".reg .pred p;\nsetp.ne.u32 p, %6, 0;\n"
               "@e mbarrier.arrive.expect_tx.shared::cta.b64 _, [%2], 16384;\n"
               "@p nanosleep.u32 128;\n"
               "@e cp.async.bulk.tensor.3d.shared::cluster.global.mbarrier::complete_tx::bytes [%0], [%1, {%3, %4, %5}], [%2];\n}"
               ::"r"(dst), "l"(m), "r"(bar), "r"(c0), "r"(c1), "r"(c2), "r"((uint32_t)pace) : "memory");
}
__device__ __forceinline__ void arrive_mapped_e(uint32_t cluster_addr) {
  asm volatile(ELECT_BEGIN "@e mbarrier.arrive.shared::cluster.b64 _, [%0];\n}" ::"r"(cluster_addr) : "memory");
}
__device__ __forceinline__ void arrive_e(uint32_t bar) {
  asm volatile(ELECT_BEGIN "@e mbarrier.arrive.shared::cta.b64 _, [%0];\n}" ::"r"(bar) : "memory");
}
__device__ __forceinline__ void bulk_commit() { asm volatile("cp.async.bulk.commit_group;" ::: "memory"); }
template <int N> __device__ __forceinline__ void bulk_wait() { asm volatile("cp.async.bulk.wait_group %0;" ::"n"(N) : "memory"); }
__device__ __forceinline__ void wg_fence() { asm volatile("wgmma.fence.sync.aligned;" ::: "memory"); }
__device__ __forceinline__ void wg_commit() { asm volatile("wgmma.commit_group.sync.aligned;" ::: "memory"); }
template <int N> __device__ __forceinline__ void wg_wait() { asm volatile("wgmma.wait_group.sync.aligned %0;" ::"n"(N) : "memory"); }
__device__ __forceinline__ void fence_async_global() { asm volatile("fence.proxy.async.global;" ::: "memory"); }
__device__ __forceinline__ void st_relaxed(unsigned int* p, unsigned int v) {
  asm volatile("st.relaxed.gpu.global.u32 [%0], %1;" ::"l"(p), "r"(v) : "memory");
}
__device__ __forceinline__ void ldsm4(uint32_t* r, uint32_t addr) {
  asm volatile("ldmatrix.sync.aligned.m8n8.x4.shared.b16 {%0, %1, %2, %3}, [%4];"
               : "=r"(r[0]), "=r"(r[1]), "=r"(r[2]), "=r"(r[3]) : "r"(addr) : "memory");
}
__device__ __forceinline__ void stsm4(uint32_t addr, const uint32_t* r) {
  asm volatile("stmatrix.sync.aligned.m8n8.x4.shared.b16 [%0], {%1, %2, %3, %4};"
               ::"r"(addr), "r"(r[0]), "r"(r[1]), "r"(r[2]), "r"(r[3]) : "memory");
}
template <bool V> struct Flag { static constexpr bool value = V; };
template <int V> struct Int { static constexpr int value = V; };
__device__ __forceinline__ void fence_async_smem() { asm volatile("fence.proxy.async.shared::cta;" ::: "memory"); }
__device__ __forceinline__ void cluster_arrive_relaxed() { asm volatile("barrier.cluster.arrive.relaxed.aligned;" ::: "memory"); }
__device__ __forceinline__ void cluster_wait() { asm volatile("barrier.cluster.wait.acquire.aligned;" ::: "memory"); }
__device__ __forceinline__ void prefetch_map(const CUtensorMap* m) {
  asm volatile("prefetch.tensormap [%0];" ::"l"(m) : "memory");
}
__device__ __forceinline__ void prefetch_map_e(const CUtensorMap* m) {
  asm volatile(ELECT_BEGIN "@e prefetch.tensormap [%0];\n}" ::"l"(m) : "memory");
}
__device__ __forceinline__ void poll_flag(const unsigned int* ptr, unsigned int target) {
  asm volatile(
      "{\n.reg .pred p;\n.reg .u32 c;\n.reg .s32 v;\n"
      "mov.u32 c, 0;\n"
      "LOOP:\n"
      "ld.acquire.gpu.global.s32 v, [%0];\n"
      "sub.s32 v, v, %1;\n"
      "setp.ge.s32 p, v, 0;\n"
      "@p bra DONE;\n"
      "add.u32 c, c, 1;\n"
      "setp.lt.u32 p, c, 1048576;\n"
      "@p bra LOOP;\n"
      "trap;\n"
      "DONE:\n}"
      ::"l"(ptr), "r"(target) : "memory");
}

constexpr uint32_t DESC_HI = (1024u >> 4) | (1u << 30);
__device__ __forceinline__ uint64_t desc(uint32_t lo) { return ((uint64_t)DESC_HI << 32) | lo; }
constexpr uint32_t DESC_A_LBO = 1u << 16;
constexpr uint32_t DESC_B_LBO = (4096u >> 4) << 16;

__device__ __forceinline__ int kgroup_col(int j, int q) {
  return q == 0 ? j : (q == 1 ? (j ^ 1) : (((j ^ 2) & ~1) + (q - 2)));
}

__device__ __forceinline__ int role_of_cluster(int c) {
  const int a = c - 4;
  const int b = c - 36, r = (b * 37) >> 8;
  const int first = (a & ~7) + (a & 3) * 2 + ((a >> 2) & 1);
  const int second = 32 + r * 8 + ((0x7531640 >> (((b - r * 7) * 4) & 31)) & 7);
  return c >= 2 * kGroups ? c : (c >= 36 ? second : (c >= 4 ? first : 34 + c * 8));
}
__device__ __forceinline__ int helped_round(int grp) { return (grp & 2) ? (grp & 3) - 1 : 3; }
__device__ __forceinline__ int job_of_group(int grp) {
  return (grp & 2) ? (grp & 1) * 8 + (grp >> 2) : 16 + (grp >> 2) * 2 + (grp & 1);
}
__device__ __forceinline__ int job_row(int n) {
  const int grp = n < 16 ? (n & 7) * 4 + 2 + (n >> 3) : ((n - 16) >> 1) * 4 + (n & 1);
  return (helped_round(grp) * kGroups + grp) * 128;
}

constexpr int PROF_SMEM = 0;
#define PROF_BOTH(idx) do {} while (0)
#define PROF_SVC(idx) do {} while (0)
#define PROF_DUMP() do {} while (0)
#define PROF(idx) do {} while (0)
#define PROF_ST(idx) do {} while (0)
#define PROF_SKEW(idx) do {} while (0)

__global__ void __cluster_dims__(2, 1, 1) __launch_bounds__(384, 1)
dcn_kernel(const __nv_bfloat16* __restrict__ xptr, const __nv_bfloat16* __restrict__ wptr,
           const __nv_bfloat16* __restrict__ bias, __nv_bfloat16* optr,
           const __grid_constant__ CUtensorMap mx64, const __grid_constant__ CUtensorMap mx32,
           const __grid_constant__ CUtensorMap mo64, const __grid_constant__ CUtensorMap mo32,
           const __grid_constant__ CUtensorMap mw, const __grid_constant__ CUtensorMap mp) {
  extern __shared__ __align__(1024) uint8_t smem_raw[];
  const uint32_t sb = smem_u32(smem_raw);
  const int tid = threadIdx.x;
  if ((tid >> 5) == 8) PROF_ST(0);
  if ((tid >> 5) == 9) PROF_BOTH(48);
  const int wid = __shfl_sync(0xffffffffu, tid >> 5, 0);
  if (wid == 0) {
    asm volatile("prefetch.global.L2 [%0];" ::"l"(wptr + ((blockIdx.x & 31) * 32 + tid) * 64));
    asm volatile("prefetch.global.L2 [%0];" ::"l"(xptr + ((blockIdx.x & 127) * 32 + tid) * kDim));
    prefetch_map_e(&mw);
    prefetch_map_e(&mx64);
    PROF_ST(29);
  }
  const int bid = role_of_cluster(blockIdx.x >> 1) * 2 + (blockIdx.x & 1);
  const int j = bid & 3;
  const int grp = bid >> 2;
  const bool helper = grp == kGroups;
  const int col0 = helper ? kgroup_col(j, 2) * 256 : 0;
  const int row0 = helper ? job_row(0) : grp * 128;
  auto first_loads = [&](int s) {
    const int col = col0 + s * 64;
    expect_load_3d_e(sb + OFF_B + 2 * s * B_SLOT, &mw, sb + BAR_BFULL0 + 2 * s * 8, 0, col, j * 4);
    expect_load_2d_e<false>(sb + OFF_A + s * A_SLOT, &mx64, sb + BAR_AFULL + s * 8, col, row0);
    expect_load_3d_e(sb + OFF_B + (2 * s + 1) * B_SLOT, &mw, sb + BAR_BFULL0 + (2 * s + 1) * 8, 0, col + 32, j * 4);
    expect_load_2d_e<false>(sb + OFF_A + (NA + s) * A_SLOT, &mx64, sb + BAR_AFULL + (NA + s) * 8, col, row0 + 64);
    PROF_ST(2 + s);
  };
  auto init_full = [&](int s) {
    mbar_init(sb + BAR_BFULL0 + 2 * s * 8, 1);
    mbar_init(sb + BAR_BFULL0 + (2 * s + 1) * 8, 1);
    mbar_init(sb + BAR_AFULL + s * 8, 1);
    mbar_init(sb + BAR_AFULL + (NA + s) * 8, 1);
  };
  if (wid == 8) {
    PROF_ST(28);
    if (tid == 256) {
      init_full(0);
      asm volatile("fence.mbarrier_init.release.cluster;" ::: "memory");
    }
    __syncwarp();
    PROF_ST(1);
    first_loads(0);
    if (tid == 256) {
#pragma unroll
      for (int s = 1; s < 4; s++) init_full(s);
      asm volatile("fence.mbarrier_init.release.cluster;" ::: "memory");
    }
    __syncwarp();
  }
  const int wg = wid >> 2;
  const int warp = wid & 3;
  const uint32_t rank = j & 1;
  const int short_t = (gridDim.x > 4 * kGroups && !helper) ? helped_round(grp) * kLayers : -8;
  const unsigned lend = helper ? ~0u : 1u;
  auto moves_up = [&](int t) { return (unsigned)(t + 1 - short_t) > lend; };

  if (wg == 2) {
    asm volatile("setmaxnreg.dec.sync.aligned.u32 40;");
    if (tid == 288) {
      if (sb & 1023) asm volatile("trap;");
#pragma unroll
      for (int i = 0; i < NB; i++) { mbar_init(sb + BAR_BFULL + i * 8, 1); mbar_init(sb + BAR_BEMPTY + i * 8, 2); }
#pragma unroll
      for (int i = 0; i < 4; i++) mbar_init(sb + BAR_XREADY + i * 8, 1);
      mbar_init(sb + BAR_ORDER, 1);
    } else if (tid == 320) {
#pragma unroll
      for (int i = 0; i < 2 * NA; i++) { mbar_init(sb + BAR_AEMPTY + i * 8, 2); mbar_init(sb + BAR_STAGED + i * 8, 4); }
    } else if (tid == 352) {
#pragma unroll
      for (int i = 0; i < 8; i++) { mbar_init(sb + BAR_PFULL + i * 8, 1); mbar_init(sb + BAR_PFREE + i * 8, 1); }
      mbar_init(sb + BAR_BIAS, 32);
      asm volatile("st.shared.v2.u32 [%0], {0, 0};" ::"r"(sb + OFF_DELAY) : "memory");
    }
    asm volatile("fence.mbarrier_init.release.cluster;" ::: "memory");
    __syncwarp();
    cluster_arrive_relaxed();
    if (warp == 0) {
      PROF_ST(6);
#pragma unroll 1
      for (int s = 1; s < 4; s++) first_loads(s);
      cluster_wait();
      PROF_ST(7);
      uint32_t par = 0;
      int l = 0;
      const int ntiles = helper ? kJobs : kTiles;
#pragma unroll 1
      for (int t = 0; t < ntiles; t++) {
        const int jo = (t == 0 && !helper) ? 0 : j;
        const int q_end = t == short_t ? 2 : 4;
#pragma unroll 1
        for (int q = (helper ? 2 : 0) + (t == 0); q < q_end; q++) {
          const int krow = l * kDim + kgroup_col(jo, q) * 256;
          const bool first = q == (helper ? 2 : 0);
          const bool up = q >= 2 && moves_up(t);
          const int shift = first ? (moves_up(t - 1) ? -1 : 0) : (up && q == 2 ? 1 : 0);
          const int paced = first ? (shift ? DRAIN + 1 : 0) : ((helper || (q == 1 && (t == short_t || t == 0))) ? 0 : NB);
          const uint32_t dst = sb + OFF_B + (up ? B_SLOT : 0);
          const uint32_t full = sb + (first ? BAR_BFULL0 : BAR_BFULL);
          if (shift > 0) mbar_spin(sb + BAR_BEMPTY, par);
#pragma unroll 1
          for (int i = 0; i < NB; i++) {
            if ((unsigned)(i + shift) < NB) mbar_spin(sb + BAR_BEMPTY + (i + shift) * 8, par);
            paced_load_3d_e(dst + i * B_SLOT, &mw, full + i * 8, 0, krow + i * 32, j * 4, i < paced);
            PROF_SKEW(t * 32 + q * 8 + i);
          }
          if (shift < 0) mbar_spin(sb + BAR_BEMPTY + (NB - 1) * 8, par);
          par ^= 1;
        }
        if (helper || ++l == kLayers) l = 0;
      }
    } else if (warp <= 2) {
      const int w = warp - 1;
      const uint32_t abase = sb + OFF_A + w * NA * A_SLOT;
      const uint32_t fullb = sb + BAR_AFULL + w * NA * 8;
      const uint32_t emptyb = sb + BAR_AEMPTY + w * 8;
      const uint32_t stagedb = sb + BAR_STAGED + w * NA * 8;
      const unsigned int base = __shfl_sync(0xffffffffu, *(volatile unsigned int*)(g_flags + bid * 32), 0);
      cluster_wait();
      uint32_t epar = 0;
      uint32_t spar = 0;
      auto refill = [&](const CUtensorMap* m, int col, int row) {
#pragma unroll 1
        for (int s = 0; s < 4; s++) {
          mbar_spin(emptyb + s * 16, epar);
          expect_load_2d_e<false>(abase + s * A_SLOT, m, fullb + s * 8, col + s * 64, row);
        }
        epar ^= 1;
      };
      auto store_refill = [&](int out_row, int col, int row, bool last_read) {
#pragma unroll 1
        for (int s = 0; s < 4; s++) {
          mbar_spin(stagedb + s * 8, spar);
          fence_async_smem();
          store_2d_e<true>(&mo64, abase + s * A_SLOT, j * 256 + s * 64, out_row);
          bulk_commit();
          bulk_wait<0>();
          __syncwarp();
          mbar_spin(emptyb + s * 16, epar);
          if (last_read) expect_load_2d_e<true>(abase + s * A_SLOT, &mx64, fullb + s * 8, col + s * 64, row);
          else expect_load_2d_e<false>(abase + s * A_SLOT, &mx64, fullb + s * 8, col + s * 64, row);
        }
        spar ^= 1;
        epar ^= 1;
      };
      auto store_tile = [&](auto stream, int out_row) {
#pragma unroll 1
        for (int c = 0; c < 4; c++) {
          mbar_spin(stagedb + c * 8, spar);
          fence_async_smem();
          arrive_e(fullb + c * 8);
          if (!decltype(stream)::value && w == 1) {
            bulk_commit();
            bulk_wait<0>();
          }
          store_2d_e<decltype(stream)::value>(&mo64, abase + c * A_SLOT, j * 256 + c * 64, out_row);
        }
        spar ^= 1;
        bulk_commit();
        bulk_wait<0>();
        __syncwarp();
      };
      auto refill_shared = [&](const CUtensorMap* m32, int col, int row) {
#pragma unroll 1
        for (int s = 0; s < 4; s++) {
          mbar_spin(emptyb + s * 16, epar);
          expect_load_2d_mc_e(abase + s * A_SLOT + rank * 4096, m32, fullb + s * 8, col + s * 64, row + rank * 32);
        }
        epar ^= 1;
      };
      if (helper) {
#pragma unroll 1
        for (int h = 1; h < 2 * kJobs; h++) refill_shared(&mx32, col0 + (h & 1) * 256, job_row(h >> 1) + w * 64);
      } else {
        const uint32_t xready_peer = map_cta(sb + BAR_XREADY + w * 8, rank ^ 1);
        const unsigned int* oflag = g_flags + (grp * 4 + kgroup_col(j, 2)) * 32;
        unsigned int* done_mine = g_flags + kFlagSet + (bid * 2 + w) * 32;
        const unsigned int* done_peer = g_flags + kFlagSet + ((bid ^ 2) * 2 + w) * 32;
        uint32_t nx = 0;
#pragma unroll 1
        for (int rd = 0; rd < kRounds; rd++) {
          const int xrow = (rd * kGroups + grp) * 128 + w * 64;
          if (rd == 0) {
            refill(&mx64, 256, xrow);
          } else {
            poll_flag(done_peer, base + nx);
            store_refill(xrow - kGroups * 128, (j ^ 1) * 256, xrow, rd * kLayers == short_t);
          }
          if (rd * kLayers != short_t) {
#pragma unroll 1
            for (int h = 0; h < 2; h++) refill_shared(&mx32, (kgroup_col(rd == 0 ? 0 : j, 2) + h) * 256, xrow);
          }
#pragma unroll 1
          for (int l = 1; l < kLayers; l++) {
            if (l > 1) poll_flag(done_peer, base + nx);
            store_tile(Flag<false>(), xrow);
            PROF_SVC((rd * kLayers + l - 1) * 2 + w);
            arrive_mapped_e(xready_peer);
            arrive_e(sb + BAR_PUB + w * 8);
            mbar_spin(sb + BAR_XREADY + w * 8, nx & 1);
            fence_async_global();
            refill(&mo64, (j ^ 1) * 256, xrow);
#pragma unroll 1
            for (int h = 0; h < 2; h++) {
              poll_flag(oflag + h * 32, base + nx + 1);
              fence_async_global();
              refill_shared(&mo32, (kgroup_col(j, 2) + h) * 256, xrow);
            }
            if (rank) {
#pragma unroll 1
              for (int s = 0; s < 4; s++) mbar_spin(fullb + s * 8, 1);
            }
            nx++;
            if ((tid & 31) == 0) st_relaxed(done_mine, base + (nx == kRounds * (kLayers - 1) ? kEpoch : nx));
            __syncwarp();
          }
          const int nrow = xrow + kGroups * 128;
          if (rd + 1 == kRounds) {
            poll_flag(done_peer, base + nx);
            store_tile(Flag<true>(), xrow);
            PROF_SVC((rd * kLayers + kLayers - 1) * 2 + w);
            arrive_e(sb + BAR_PUB + w * 8);
          } else {
            refill(&mx64, j * 256, nrow);
            PROF_SVC((rd * kLayers + kLayers - 1) * 2 + w);
          }
        }
      }
    } else {
      const int lane = tid & 31;
      unsigned int* myflag = g_flags + bid * 32;
      if (lane == 0) { prefetch_map(&mx32); prefetch_map(&mo64); prefetch_map(&mo32); }
      const unsigned int base = *(volatile unsigned int*)myflag;
      auto publish = [&](uint32_t n, uint32_t value) {
#pragma unroll 1
        for (int w = 0; w < 2; w++) mbar_wait(sb + BAR_PUB + w * 8, n & 1);
        if (lane == 0) asm volatile("st.release.gpu.global.u32 [%0], %1;" ::"l"(myflag), "r"(base + value) : "memory");
        __syncwarp();
      };
      if (helper) {
        cluster_wait();
#pragma unroll 1
        for (int n = 0; n < kJobs; n++) {
          if (n + 2 < kJobs) {
            const int row = job_row(n + 2);
#pragma unroll 1
            for (int i = 0; i < 8; i++) prefetch_2d_e(&mx64, col0 + rank * 256 + (i & 3) * 64, row + (i >> 2) * 64);
          }
          publish(n, n + 1);
        }
      } else {
        {
          float c[8];
#pragma unroll
          for (int i = 0; i < 8; i++) c[i] = 0.f;
#pragma unroll 1
          for (int l = 0; l < kLayers; l++) {
            const uint4 v = *reinterpret_cast<const uint4*>(bias + l * kDim + j * 256 + lane * 8);
            const uint32_t u[4] = {v.x, v.y, v.z, v.w};
#pragma unroll
            for (int i = 0; i < 4; i++) {
              c[2 * i] += __uint_as_float(u[i] << 16) + kTrunc;
              c[2 * i + 1] += __uint_as_float(u[i] & 0xffff0000u) + kTrunc;
              uint32_t pk;
              asm("cvt.rn.bf16x2.f32 %0, %1, %2;" : "=r"(pk) : "f"(c[2 * i + 1]), "f"(c[2 * i]));
              asm volatile("st.shared.u32 [%0], %1;" ::"r"(sb + OFF_BIAS + l * 512 + (lane >> 2) * 64 + i * 16 + (lane & 3) * 4),
                           "r"(pk) : "memory");
            }
          }
#pragma unroll
          for (int i = 0; i < 15; i++) {
            const uint32_t one = (lane >> 3) == (lane & 3) ? 0x3f80u << ((lane & 4) * 4) : 0u;
            asm volatile("st.shared.u32 [%0], %1;" ::"r"(sb + OFF_UNIT + i * 128 + lane * 4), "r"(i == 7 ? one : 0u) : "memory");
          }
          fence_async_smem();
          mbar_arrive(sb + BAR_BIAS);
        }
        const __nv_bfloat16* wslice = wptr + bid * 8192;
        cluster_wait();
        prefetch_1d_e(wslice + kDim * kDim, 16384);
        uint32_t nx = 0;
#pragma unroll 1
        for (int rd = 0; rd < kRounds; rd++) {
#pragma unroll 1
          for (int l = 1; l < kLayers; l++) {
            const int t = rd * kLayers + l;
            const bool align = ((kAlign >> t) & 1) &&
                               mbar_watch(sb + BAR_STAGED + NA * 8, (t - 1) & 1, sb + BAR_PUB + 8, nx & 1);
            uint32_t mine = 0, tick = 0;
            if (align) {
              uint32_t c0, c1;
              asm volatile("mov.u32 %0, %%clock;\nnanosleep.u32 128;\nmov.u32 %1, %%clock;\nmov.u32 %2, %%globaltimer_lo;\n"
                           "nanosleep.u32 128;\nmov.u32 %3, %%clock;"
                           : "=r"(c0), "=r"(c1), "=r"(mine), "=r"(tick) :: "memory");
              tick -= c1;
              mine = ((mine + 64) >> 8 << 10) - (c1 - c0);
            }
            publish(nx, nx + 1 == kRounds * (kLayers - 1) ? kEpoch : nx + 1);
            nx++;
            {
              uint32_t delay = 0;
              if (align) {
                unsigned int* line = g_phase + (bid & 15) * 32;
                if (lane == 0) st_relaxed(line + (grp >> 2), mine);
                __syncwarp();
#pragma unroll 1
                for (int i = 0; i < 3; i++) __nanosleep(256);
                uint32_t other;
                asm volatile("ld.relaxed.gpu.global.u32 %0, [%1];" : "=r"(other) : "l"(line + (lane & 7)) : "memory");
                const int ticks = (int)(((other + 1023) & ~1023u) - ((mine + 1023) & ~1023u)) >> 10;
                const int lag = ticks * (int)tick - (int)((-other & 1023) - (-mine & 1023));
                const int far = __reduce_max_sync(0xffffffffu, ((unsigned)ticks < 4 && lag < 700) ? lag : 0);
                delay = far > 40 ? far + 280 : 0;
              }
              asm volatile("st.relaxed.cta.shared.u32 [%0], %1;" ::"r"(sb + OFF_DELAY), "r"(delay) : "memory");
            }
            if (l < kLayers - 1 && rd == 0) prefetch_1d_e(wslice + (l + 1) * kDim * kDim, 16384);
            if (l > 1 && rd + 1 < kRounds) {
              const int nrow = ((rd + 1) * kGroups + grp) * 128;
              prefetch_1d_e(xptr + (size_t)(nrow + j * 32 + l * 8 - 16) * kDim, 8192);
              __nanosleep(600);
              prefetch_1d_e(xptr + (size_t)(nrow + j * 32 + l * 8 - 12) * kDim, 8192);
              if (rd * kLayers + l + 1 == short_t) {
                poll_flag(g_flags + (4 * kGroups + j) * 32, base + job_of_group(grp) + 1);
                fence_async_global();
                constexpr uint32_t order = 0x76325140;
#pragma unroll 1
                for (int i = NP; i < 8; i++)
                  prefetch_2d_e(&mp, j * 256 + ((order >> (i * 4)) & 3) * 64, nrow + ((order >> (i * 4)) & 4) * 16);
#pragma unroll 1
                for (int i = 0; i < 8; i++) {
                  if (i >= NP) mbar_wait(sb + BAR_PFREE + (i - NP) * 8, 0);
                  PROF(776 + i);
                  expect_load_2d_e<true>(sb + OFF_P + (i % NP) * A_SLOT, &mp, sb + BAR_PFULL + i * 8,
                                         j * 256 + ((order >> (i * 4)) & 3) * 64, nrow + ((order >> (i * 4)) & 4) * 16);
                }
              }
            }
          }
        }
#pragma unroll 1
        for (int w = 0; w < 2; w++) mbar_wait(sb + BAR_PUB + w * 8, nx & 1);
      }
    }
    if (warp == 3) PROF_DUMP();
  } else {
    float acc[128];
    const uint32_t init = sb + OFF_INIT + wid * 16;
    auto reset = [&](int T) {
#pragma unroll
      for (int i = T * 8; i < T * 8 + 8; i += 4)
        asm volatile("ld.volatile.shared.v4.f32 {%0, %1, %2, %3}, [%4];"
                     : "=f"(acc[i]), "=f"(acc[i + 1]), "=f"(acc[i + 2]), "=f"(acc[i + 3]) : "r"(init));
    };
    if ((tid & 31) == 0) asm volatile("st.volatile.shared.v4.f32 [%0], {%1, %1, %1, %1};" ::"r"(init), "f"(kOffset) : "memory");
    __syncwarp();
#pragma unroll
    for (int T = 0; T < 16; T++) reset(T);
    cluster_arrive_relaxed();
    asm volatile("setmaxnreg.inc.sync.aligned.u32 232;");
    PROF_ST(32);
    const int lane = tid & 31;
    const int wtid = tid & 127;
    const uint32_t abase = sb + OFF_A + wg * NA * A_SLOT;
    const uint32_t afull = sb + BAR_AFULL + wg * NA * 8;
    const uint32_t rel = map_cta(sb + (wtid == 64 ? BAR_BEMPTY : BAR_AEMPTY + wg * 8 - 8), wtid == 32 ? (rank ^ 1) : rank);
    const bool rel_b = wtid == 64;
    const bool rel_ab = (wtid & 31) == 0 && wtid < 96;
    const uint32_t frag0 = __shfl_sync(0xffffffffu, abase + ((wtid >> 5) * 16 + ((lane >> 3) & 1) * 8 + (lane & 7)) * 128 +
                                                        (((lane >> 4) ^ (lane & 7)) << 4), lane);
    const uint64_t adesc0 = desc(((abase & 0x3FFFF) >> 4) | DESC_A_LBO);
    const uint64_t bdesc0 = desc((((sb + OFF_B) & 0x3FFFF) >> 4) | DESC_B_LBO);

    const uint64_t zero = gridDim.y - 1;
    uint64_t adesc_q = adesc0 + zero, bdesc_q = bdesc0 + zero;

    uint32_t xr[64];
#pragma unroll
    for (int i = 0; i < 64; i++) xr[i] = 0;
    int l = 0;
    bool hold = false;
    bool swap = false;
    bool brief = helper;
    int capture_q = helper ? -1 : j;

    auto release = [&](int i, bool with_a) {
      mbar_arrive_mapped_if(rel + i * 8, (i & 1) ? with_a : rel_b);
    };
    auto chunk_staged = [&](int c) {
      __syncwarp();
      arrive_e(sb + BAR_STAGED + (wg * NA + c) * 8);
    };
    auto capture_slot = [&](int p) {
#pragma unroll
      for (int g = 0; g < 4; g++) ldsm4(&xr[(p * 4 + g) * 4], (frag0 ^ (g * 32)) + p * A_SLOT);
    };
    auto swap_half = [&](int p, int half) {
#pragma unroll
      for (int g = half * 2; g < half * 2 + 2; g++) {
        const uint32_t addr = (frag0 ^ (g * 32)) + p * A_SLOT;
        uint32_t n[4];
        ldsm4(n, addr);
        stsm4(addr, &xr[(p * 4 + g) * 4]);
#pragma unroll
        for (int i = 0; i < 4; i++) xr[(p * 4 + g) * 4 + i] = n[i];
      }
      if (half) chunk_staged(p);
    };
    auto chunk_of = [&](int c) { return wg ? (0x7631 >> (c * 4)) & 7 : (0x5420 >> (c * 4)) & 7; };
    auto add_partial = [&](int c) __attribute__((always_inline)) {
      const int n = chunk_of(c);
      const int slot = wg ? (0x1001 >> (c * 4)) & 3 : (0x2120 >> (c * 4)) & 3;
      PROF(768 + wg * 16 + c * 2);
      mbar_spin(sb + BAR_PFULL + n * 8, 0);
      PROF(768 + wg * 16 + c * 2 + 1);
      wg_fence();
      wgmma_n256(acc, ((uint64_t)(128 >> 4) << 32) | ((128 >> 4) << 16) | (((sb + OFF_UNIT + (6 - 2 * c) * 128) & 0x3FFFF) >> 4),
                 ((uint64_t)(256 >> 4) << 32) | ((128 >> 4) << 16) | (((sb + OFF_P + slot * A_SLOT) & 0x3FFFF) >> 4));
    };
    auto issue = [&](int i, int q, int t, bool wait_b) __attribute__((always_inline)) {
      if (!(i & 1)) mbar_spin(afull + (i >> 1) * 8, q & 1);
      if (wait_b) mbar_spin(sb + (q ? BAR_BFULL : BAR_BFULL0) + i * 8, (q ? q ^ t ^ 1 : t) & 1);
      const uint64_t adesc = adesc_q + ((i >> 1) * (A_SLOT >> 4) + (i & 1) * 4);
      const uint64_t bdesc = bdesc_q + i * (B_SLOT >> 4);
      wg_fence();
      wgmma_n256(acc, adesc, bdesc);
      wgmma_n256(acc, adesc + 2, bdesc + 128);
      wg_commit();
      if (i == NB - 1) { adesc_q += zero; bdesc_q += zero; }
    };
    auto retire = [&](int i, bool with_a) {
      wg_wait<2>();
      release((i + 6) & 7, with_a);
    };
    auto k_loop = [&](auto first, int t) __attribute__((always_inline)) {
      constexpr bool FIRST = decltype(first)::value;
      const bool inject = FIRST && brief && !helper;
      const uint32_t up = moves_up(t) ? B_SLOT >> 4 : 0;
      auto extras = [&](int q, int i, bool swap_now) __attribute__((always_inline)) {
        if (!FIRST) return;
        if (swap_now) swap_half(((i + 5) >> 1) & 3, (i + 1) & 1);
        if (!(i & 1) && q == capture_q) capture_slot(i >> 1);
      };
      auto free_partial = [&](int c) {
        if (FIRST) mbar_arrive_if(sb + BAR_PFREE + chunk_of(c) * 8, inject && rel_b);
      };
      extras(0, 0, false);
#pragma unroll
      for (int i = 1; i < 8; i++) {
        if (!(i & 1)) PROF(t * 32 + wg * 16 + 8 + (i >> 1));
        if ((i == 1 || i == 7) && inject) add_partial(i >> 2);
        issue(i, 0, t, true);
        if (i >= 2) retire(i, rel_ab);
        if (i == 3) free_partial(0);
        extras(0, i, i >= 3 && swap);
      }
      PROF(t * 32 + wg * 16 + 1);
      if (!FIRST || !brief) {
#pragma unroll 1
        for (int q = 1; q < 3; q++) {
#pragma unroll
          for (int i = 0; i < 8; i++) {
            issue(i, q | 4, t, true);
            if (i == 0) PROF(t * 32 + wg * 16 + 3 + q);
            retire(i, rel_ab);
            extras(q, i, i < 3 && swap);
          }
          if (FIRST) swap = false;
          if (q == 1) bdesc_q += up;
        }
      }
      const bool rel_last = rel_b | (hold & rel_ab);
      auto with_a = [&](int slot) { return slot == 7 ? rel_ab : rel_last; };
      uint32_t delay = 0;
      constexpr int JOIN = DRAIN + 2;
      constexpr int INJ = JOIN < 3 ? 3 : JOIN;
#pragma unroll
      for (int i = 0; i < DRAIN; i++) {
        issue(i, 3, t, true);
        retire(i, with_a((i + 6) & 7));
        if (i == 1) free_partial(1);
        extras(3, i, i < 3 && swap);
      }
      if (wg == 1) {
        wg_wait<1>();
        release((DRAIN + 6) & 7, with_a((DRAIN + 6) & 7));
        wg_wait<0>();
        release((DRAIN + 7) & 7, with_a((DRAIN + 7) & 7));
        if (DRAIN < 2) free_partial(1);
        PROF(t * 32 + wg * 16 + 12);
#pragma unroll
        for (int i = DRAIN; i < 3; i++) extras(-2, i, swap);
        mbar_spin(sb + BAR_ORDER, t & 1);
        PROF(t * 32 + wg * 16 + 6);
#pragma unroll
        for (int i = DRAIN; i < JOIN; i++) {
          issue(i, 3, t, true);
          extras(3, i, false);
        }
      } else {
        PROF(t * 32 + wg * 16 + 6);
#pragma unroll
        for (int i = DRAIN; i < JOIN; i++) {
          issue(i, 3, t, true);
          retire(i, with_a((i + 6) & 7));
          if (i == 1) free_partial(1);
          extras(3, i, i < 3 && swap);
        }
      }
#pragma unroll
      for (int i = JOIN; i < 8; i++) {
        if ((i == INJ || i == 7) && inject) add_partial(i == INJ ? 2 : 3);
        if (!FIRST && i == 3) asm volatile("ld.relaxed.cta.shared.u32 %0, [%1];" : "=r"(delay) : "r"(sb + OFF_DELAY + wg * 4) : "memory");
        if (!FIRST && i == 5) {
          asm volatile("{\n.reg .pred p;\n.reg .u32 a, b;\nsetp.eq.u32 p, %0, 0;\n@p bra.uni DONE;\nmov.u32 a, %%clock;\n"
                       "WAIT:\nmov.u32 b, %%clock;\nsub.u32 b, b, a;\nsetp.lt.u32 p, b, %0;\n@p bra.uni WAIT;\nDONE:\n}" ::"r"(delay) : "memory");
        }
        issue(i, 3, t, true);
        if (i == 7) mbar_arrive_if(sb + BAR_ORDER, rel_b & (wg == 0));
        retire(i, rel_last);
        if (i == INJ + 2) free_partial(2);
        extras(3, i, false);
      }
      bdesc_q -= up;
    };

    auto epilogue = [&](auto kind, int t, bool more) __attribute__((always_inline)) {
      constexpr int KIND = decltype(kind)::value;
      constexpr int PRE = KIND == 0 ? BPRE : (KIND == 1 ? HPRE : 0);
      if (KIND == 0 && t == 0) mbar_spin(sb + BAR_BIAS, 0);
      const uint32_t bl = sb + OFF_BIAS + (KIND == 1 ? kLayers - 1 : l) * 512 + ((frag0 >> 3) & 0x30);
      uint32_t bq[8][4];
      auto load_bias = [&](int U) {
        asm volatile("ld.shared.v4.u32 {%0, %1, %2, %3}, [%4];"
                     : "=r"(bq[U][0]), "=r"(bq[U][1]), "=r"(bq[U][2]), "=r"(bq[U][3]) : "r"(bl + U * 64));
      };
#pragma unroll
      for (int U = 0; U < PRE; U++) load_bias(U);
      wg_wait<1>();
      release(6, false);
      if (more) mbar_spin(sb + BAR_BFULL0, (t + 1) & 1);
      wg_wait<0>();
#pragma unroll
      for (int i = 0; i < 128; i++) asm volatile("" : "+f"(acc[i]) :: "memory");
      release(7, KIND == 0 ? rel_b : (KIND == 1 ? rel_ab : rel_b | (more & rel_ab)));
      PROF(t * 32 + wg * 16 + 2);
      if (t == 0) PROF_ST(30 + wg);

      auto pack = [&](int i, float off) {
        uint32_t v;
        asm("cvt.rn.bf16x2.f32 %0, %1, %2;" : "=r"(v) : "f"(acc[i * 2 + 1] - off), "f"(acc[i * 2] - off));
        return v;
      };
      auto cross = [&](int T, int i, float off) {
        uint32_t s2 = pack(T * 4 + i, off), o;
        asm("add.rn.bf16x2 %0, %1, %2;" : "=r"(s2) : "r"(s2), "r"(bq[T >> 1][(T & 1) * 2 + (i >> 1)]));
        asm("fma.rn.bf16x2 %0, %1, %2, %1;" : "=r"(o) : "r"(xr[T * 4 + i]), "r"(s2));
        return o;
      };
      auto offset_for = [&](int T) { return T >= LAG ? acc[(T - LAG) * 8 + 7] : kOffset; };
      if (KIND == 2) {
        uint32_t id;
        asm volatile("mov.u32 %0, %%tid.x;" : "=r"(id));
        __nv_bfloat16* dst = optr + (size_t)(job_row(t) + wg * 64) * kDim + j * 256 + (id & 127) * 2;
        uint64_t pol;
        asm volatile("createpolicy.fractional.L2::evict_first.b64 %0, 1.0;" : "=l"(pol));
#pragma unroll
        for (int T = 0; T < 16; T++) {
#pragma unroll
          for (int i = 0; i < 4; i++)
            asm volatile("st.global.L2::cache_hint.b32 [%0], %1, %2;"
                         ::"l"(dst + (T * 4 + (i ^ 1)) * kDim), "r"(pack(T * 4 + i, offset_for(T))), "l"(pol) : "memory");
          reset(T);
        }
        asm volatile("bar.sync %0, 128;" ::"r"(wg + 1) : "memory");
        mbar_arrive_if(sb + BAR_PUB + wg * 8, rel_b);
      } else if (KIND == 1) {
#pragma unroll
        for (int T = 0; T < 16; T++) {
#pragma unroll
          for (int i = 0; i < 4; i++) xr[T * 4 + i] = cross(T, i, offset_for(T));
          if ((T & 1) && (T >> 1) + PRE < 8) load_bias((T >> 1) + PRE);
          reset(T);
        }
      } else {
#pragma unroll
        for (int T = 0; T < 16; T++) {
          uint32_t o[4];
#pragma unroll
          for (int i = 0; i < 4; i++) o[i] = cross(T, i, kOffset);
          stsm4((frag0 ^ ((T & 3) * 32)) + (T >> 2) * A_SLOT, o);
          if ((T & 3) == 3) chunk_staged(T >> 2);
          if ((T & 1) && (T >> 1) + PRE < 8) load_bias((T >> 1) + PRE);
        }
        PROF(t * 32 + wg * 16 + 7);
      }
      PROF(t * 32 + wg * 16 + 3);
    };

    PROF_ST(8);
    cluster_wait();
    PROF_ST(9);
    mbar_spin(sb + BAR_BFULL0, 0);
    PROF_ST(10);
    issue(0, 0, 0, false);
    PROF_ST(11);
    int t = 0;
#pragma unroll 1
    while (true) {
      if (t > 0) {
        if (helper) {
          epilogue(Int<2>(), t - 1, t < kJobs);
          if (t == kJobs) break;
        } else {
          epilogue(Int<1>(), t - 1, true);
        }
        issue(0, 0, 0, false);
      }
      l = 0;
      swap = t > 0 && !helper;
      brief = helper || t == short_t;
      hold = helper && t + 1 < kJobs;
      capture_q = (t > 0 || helper) ? -1 : j;
      PROF(t * 32 + wg * 16 + 0);
      k_loop(Flag<true>(), t);
      t++;
      if (helper) continue;
#pragma unroll 1
      do {
        epilogue(Int<0>(), t - 1, t < kTiles);
        if (t == kTiles) asm volatile("exit;");
        issue(0, 0, 0, false);
        l++;
        hold = l == kLayers - 1 && t + 1 < kTiles;
        PROF(t * 32 + wg * 16 + 0);
        k_loop(Flag<false>(), t);
        t++;
      } while (!hold);
    }
  }
}

__global__ void __launch_bounds__(256) dcn_fallback(const __nv_bfloat16* __restrict__ x0, const __nv_bfloat16* __restrict__ w,
                                                    const __nv_bfloat16* __restrict__ b, __nv_bfloat16* __restrict__ out) {
  __shared__ float xs[8][kDim];
  const size_t r0 = (size_t)blockIdx.x * 8;
  for (int i = threadIdx.x; i < 8 * kDim; i += 256) xs[i / kDim][i % kDim] = __bfloat162float(x0[r0 * kDim + i]);
  __syncthreads();
  for (int l = 0; l < kLayers; l++) {
    float a[4][8] = {};
    for (int k = 0; k < kDim; k++) {
#pragma unroll
      for (int c = 0; c < 4; c++) {
        const float wv = __bfloat162float(w[((size_t)l * kDim + k) * kDim + c * 256 + threadIdx.x]);
#pragma unroll
        for (int r = 0; r < 8; r++) a[c][r] += xs[r][k] * wv;
      }
    }
    __syncthreads();
#pragma unroll
    for (int c = 0; c < 4; c++) {
      const int n = c * 256 + threadIdx.x;
#pragma unroll
      for (int r = 0; r < 8; r++) {
        const float v = __bfloat162float(x0[(r0 + r) * kDim + n]) * (a[c][r] + __bfloat162float(b[l * kDim + n])) + xs[r][n];
        xs[r][n] = __bfloat162float(__float2bfloat16(v));
      }
    }
    __syncthreads();
  }
  for (int i = threadIdx.x; i < 8 * kDim; i += 256) out[r0 * kDim + i] = __float2bfloat16(xs[i / kDim][i % kDim]);
}

typedef CUresult (*EncodeFn)(CUtensorMap*, CUtensorMapDataType, cuuint32_t, void*, const cuuint64_t*, const cuuint64_t*,
                             const cuuint32_t*, const cuuint32_t*, CUtensorMapInterleave, CUtensorMapSwizzle,
                             CUtensorMapL2promotion, CUtensorMapFloatOOBfill);

static void make_map_2d(EncodeFn enc, CUtensorMap* m, void* ptr, uint64_t rows, uint32_t box_rows,
                        CUtensorMapSwizzle swizzle = CU_TENSOR_MAP_SWIZZLE_128B) {
  cuuint64_t dims[2] = {(cuuint64_t)kDim, rows};
  cuuint64_t strides[1] = {kDim * 2};
  cuuint32_t box[2] = {64, box_rows};
  cuuint32_t es[2] = {1, 1};
  enc(m, CU_TENSOR_MAP_DATA_TYPE_BFLOAT16, 2, ptr, dims, strides, box, es, CU_TENSOR_MAP_INTERLEAVE_NONE,
      swizzle, CU_TENSOR_MAP_L2_PROMOTION_L2_128B, CU_TENSOR_MAP_FLOAT_OOB_FILL_NONE);
}

}

extern "C" void kernel_launch(void* const* d_in, const int* in_sizes, int n_in, void* d_out, int out_size) {
  using namespace dcn;
  (void)in_sizes; (void)n_in; (void)out_size;
  void* fn = nullptr;
  cudaDriverEntryPointQueryResult qr;
  cudaGetDriverEntryPoint("cuTensorMapEncodeTiled", &fn, cudaEnableDefault, &qr);
  EncodeFn enc = (EncodeFn)fn;
  CUtensorMap mx64, mx32, mo64, mo32, mw, mp;
  make_map_2d(enc, &mx64, d_in[0], kRows, 64);
  make_map_2d(enc, &mx32, d_in[0], kRows, 32);
  make_map_2d(enc, &mo64, d_out, kRows, 64);
  make_map_2d(enc, &mo32, d_out, kRows, 32);
  make_map_2d(enc, &mp, d_out, kRows, 64, CU_TENSOR_MAP_SWIZZLE_NONE);
  {
    cuuint64_t dims[3] = {64, (cuuint64_t)kLayers * kDim, kDim / 64};
    cuuint64_t strides[2] = {kDim * 2, 128};
    cuuint32_t box[3] = {64, 32, 4};
    cuuint32_t es[3] = {1, 1, 1};
    enc(&mw, CU_TENSOR_MAP_DATA_TYPE_BFLOAT16, 3, d_in[1], dims, strides, box, es, CU_TENSOR_MAP_INTERLEAVE_NONE,
        CU_TENSOR_MAP_SWIZZLE_128B, CU_TENSOR_MAP_L2_PROMOTION_L2_128B, CU_TENSOR_MAP_FLOAT_OOB_FILL_NONE);
  }
  const __nv_bfloat16* x0 = (const __nv_bfloat16*)d_in[0];
  const __nv_bfloat16* w = (const __nv_bfloat16*)d_in[1];
  const __nv_bfloat16* b = (const __nv_bfloat16*)d_in[2];
  __nv_bfloat16* out = (__nv_bfloat16*)d_out;
  constexpr int smem = SMEM_BYTES + PROF_SMEM;
  cudaFuncSetAttribute(dcn_kernel, cudaFuncAttributeMaxDynamicSharedMemorySize, smem);

  cudaLaunchConfig_t cfg = {};
  cfg.gridDim = dim3(4 * kGroups + 4);
  cfg.blockDim = dim3(384);
  cfg.dynamicSmemBytes = smem;
  cudaLaunchAttribute attr;
  attr.id = cudaLaunchAttributeClusterDimension;
  attr.val.clusterDim.x = 2;
  attr.val.clusterDim.y = 1;
  attr.val.clusterDim.z = 1;
  cfg.attrs = &attr;
  cfg.numAttrs = 1;
  int clusters = 0;
  cudaOccupancyMaxActiveClusters(&clusters, dcn_kernel, &cfg);
  if (clusters >= 2 * kGroups) {
    const int grid = 4 * kGroups + (clusters >= 2 * kGroups + 2 ? 4 : 0);
    dcn_kernel<<<grid, 384, smem>>>(x0, w, b, out, mx64, mx32, mo64, mo32, mw, mp);
  } else {
    dcn_fallback<<<kRows / 8, 256>>>(x0, w, b, out);
  }
}
```
